```python
import torch

def _softmax(x, axis=-1):
    return torch.softmax(x, dim=axis)
def _gelu(x):
    return torch.nn.functional.gelu(x, approximate="tanh")
def _silu(x):
    return torch.nn.functional.silu(x)
def _sigmoid(x):
    return torch.sigmoid(x)
def _layernorm(x, axis=-1, eps=1e-5):
    m = x.mean(dim=axis, keepdim=True)
    v = x.var(dim=axis, keepdim=True, unbiased=False)
    return (x - m) / torch.sqrt(v + eps)
def _scatter_add(tgt, idx, src, axis=0):
    return tgt.clone().index_add_(axis, idx, src)
def _segment_sum(src, seg, n):
    out = torch.zeros((n,) + src.shape[1:], dtype=src.dtype)
    return out.index_add_(0, seg, src)
def _pad(x, pw):
    flat = tuple(v for pair in reversed(pw) for v in pair)
    return torch.nn.functional.pad(x, flat)

kernel_name = 'recurrent_scan__grouped_kv_mqa__glu_gated_bilinear__prompt'

def setup_inputs():

    _w = (lambda a: (lambda t: t.to(torch.bfloat16) if t.is_floating_point() else t)(torch.as_tensor(a)))
    def _A_setup():
        B, S, D, H = 1, 2048, 640, 32
        Dh = D // H
        return {
            "x": _w((lambda *s: torch.randn(*s, dtype=torch.bfloat16) * 0.05)(B, S, D)),
            "wq": _w((lambda *s: torch.randn(*s, dtype=torch.bfloat16) * 0.2)(D, H * Dh)),
            "wk": _w((lambda *s: torch.randn(*s, dtype=torch.bfloat16) * 0.2)(D, Dh)),
            "wv": _w((lambda *s: torch.randn(*s, dtype=torch.bfloat16) * 0.2)(D, Dh)),
            "wo": _w((lambda *s: torch.randn(*s, dtype=torch.bfloat16) * 0.2)(H * Dh, D)),
        }
    _A_in = _A_setup()

    def _B_setup():
        B, S, D, F = 1, 2048, 640, 1536
        return {
            "x": _w((lambda *s: torch.randn(*s, dtype=torch.bfloat16) * 0.05)(B, S, D)),
            "w_gate": _w((lambda *s: torch.randn(*s, dtype=torch.bfloat16) * 0.1)(D, F) * (D ** -0.5)),
            "w_up": _w((lambda *s: torch.randn(*s, dtype=torch.bfloat16) * 0.1)(D, F) * (D ** -0.5)),
            "w_down": _w((lambda *s: torch.randn(*s, dtype=torch.bfloat16) * 0.1)(F, D) * (F ** -0.5)),
        }
    _B_in = _B_setup()

    return {
        "A_x": _A_in["x"],
        "A_wq": _A_in["wq"],
        "A_wk": _A_in["wk"],
        "A_wv": _A_in["wv"],
        "A_wo": _A_in["wo"],
        "B_x": _B_in["x"],
        "B_w_gate": _B_in["w_gate"],
        "B_w_up": _B_in["w_up"],
        "B_w_down": _B_in["w_down"],
    }

def reference(A_x, A_wq, A_wk, A_wv, A_wo, B_x, B_w_gate, B_w_up, B_w_down):
    def _A_ref(x, wq, wk, wv, wo):
        B, S, D = x.shape
        H = 32
        Dh = D // H
        q = (lambda x, *d: x.permute(*d))((x @ wq).reshape(B, S, H, Dh), 0, 2, 1, 3)
        k = x @ wk
        v = x @ wv
        scores = torch.einsum("bhqd,bkd->bhqk", q, k) * (Dh ** -0.5)
        p = _softmax(scores, axis=-1)
        o = torch.einsum("bhqk,bkd->bhqd", p, v)
        return (lambda x, *d: x.permute(*d))(o, 0, 2, 1, 3).reshape(B, S, H * Dh) @ wo

    def _B_ref(x, w_gate, w_up, w_down):
        g = torch.einsum("bsd,df->bsf", x, w_gate)
        u = torch.einsum("bsd,df->bsf", x, w_up)
        h = g * u
        return torch.einsum("bsf,fd->bsd", h, w_down)

    x = A_x
    xn = _layernorm(x, axis=-1)
    s = _A_ref(xn, A_wq, A_wk, A_wv, A_wo)
    g = _silu(_B_ref(xn, B_w_gate, B_w_up, B_w_down))
    return x + s * g
```

```cpp
#include <cuda_runtime.h>
#include <cuda_bf16.h>
#include <cuda.h>
#include <stdint.h>

#define PMASK 0x11011101u
#define PDEG 5

namespace mk {

constexpr uint32_t XN_OFF = 0, RING_OFF = 81920, HST_OFF = 180224, QO_OFF = 196608, KVR_OFF = 206848, BAR_OFF = 231424,
                   SMEM_TOTAL = 232448;
constexpr uint32_t XT_OFF = XN_OFF + 32768;
enum { B_SLAB = 0, B_SLABFREE = 1, B_KVFULL = 2, B_KVALL = 6, B_RING = 7, B_Q2 = 10, B_OREADY = 11, B_QOFREE = 12,
       B_WO = 13, B_OBLOB = 17, B_XT = 18, NBAR = 19 };
constexpr uint32_t KVCNT_OFF = BAR_OFF + 256;

__device__ uint4 g_kv[32 * 6144 / 16];
__device__ uint4 g_h[32 * 24 * 8192 / 16];
__device__ uint4 g_o[32 * 8 * 10240 / 16];
__device__ unsigned g_flag_kv[32];
__device__ unsigned g_flag_h[32];
__device__ unsigned g_flag_o[64];
__device__ unsigned g_epoch[128];
#define PROF(i)

__device__ __forceinline__ void wgmma_rs_n24_t1(float (&d)[12], uint32_t a0, uint32_t a1, uint32_t a2, uint32_t a3, uint64_t desc, int scale_d) {
    asm volatile("{\n.reg .pred p;\nsetp.ne.b32 p, %17, 0;\n"
        "wgmma.mma_async.sync.aligned.m64n24k16.f32.bf16.bf16 {%0, %1, %2, %3, %4, %5, %6, %7, %8, %9, %10, %11}, {%12, %13, %14, %15}, %16, p, 1, 1, 1;\n}\n"
        : "+f"(d[0]), "+f"(d[1]), "+f"(d[2]), "+f"(d[3]), "+f"(d[4]), "+f"(d[5]), "+f"(d[6]), "+f"(d[7]), "+f"(d[8]), "+f"(d[9]), "+f"(d[10]), "+f"(d[11])
        : "r"(a0), "r"(a1), "r"(a2), "r"(a3), "l"(desc), "r"(scale_d));
}
__device__ __forceinline__ void wgmma_rs_n64_t0(float (&d)[32], uint32_t a0, uint32_t a1, uint32_t a2, uint32_t a3, uint64_t desc, int scale_d) {
    asm volatile("{\n.reg .pred p;\nsetp.ne.b32 p, %37, 0;\n"
        "wgmma.mma_async.sync.aligned.m64n64k16.f32.bf16.bf16 {%0, %1, %2, %3, %4, %5, %6, %7, %8, %9, %10, %11, %12, %13, %14, %15, %16, %17, %18, %19, %20, %21, %22, %23, %24, %25, %26, %27, %28, %29, %30, %31}, {%32, %33, %34, %35}, %36, p, 1, 1, 0;\n}\n"
        : "+f"(d[0]), "+f"(d[1]), "+f"(d[2]), "+f"(d[3]), "+f"(d[4]), "+f"(d[5]), "+f"(d[6]), "+f"(d[7]), "+f"(d[8]), "+f"(d[9]), "+f"(d[10]), "+f"(d[11]), "+f"(d[12]), "+f"(d[13]), "+f"(d[14]), "+f"(d[15]), "+f"(d[16]), "+f"(d[17]), "+f"(d[18]), "+f"(d[19]), "+f"(d[20]), "+f"(d[21]), "+f"(d[22]), "+f"(d[23]), "+f"(d[24]), "+f"(d[25]), "+f"(d[26]), "+f"(d[27]), "+f"(d[28]), "+f"(d[29]), "+f"(d[30]), "+f"(d[31])
        : "r"(a0), "r"(a1), "r"(a2), "r"(a3), "l"(desc), "r"(scale_d));
}
__device__ __forceinline__ void wgmma_ss_n16(float (&d)[8], uint64_t da, uint64_t db, int scale_d) {
    asm volatile("{\n.reg .pred p;\nsetp.ne.b32 p, %10, 0;\n"
        "wgmma.mma_async.sync.aligned.m64n16k16.f32.bf16.bf16 {%0, %1, %2, %3, %4, %5, %6, %7}, %8, %9, p, 1, 1, 0, 1;\n}\n"
        : "+f"(d[0]), "+f"(d[1]), "+f"(d[2]), "+f"(d[3]), "+f"(d[4]), "+f"(d[5]), "+f"(d[6]), "+f"(d[7])
        : "l"(da), "l"(db), "r"(scale_d));
}
__device__ __forceinline__ void wgmma_ss_n48(float (&d)[24], uint64_t da, uint64_t db, int scale_d) {
    asm volatile("{\n.reg .pred p;\nsetp.ne.b32 p, %26, 0;\n"
        "wgmma.mma_async.sync.aligned.m64n48k16.f32.bf16.bf16 {%0, %1, %2, %3, %4, %5, %6, %7, %8, %9, %10, %11, %12, %13, %14, %15, %16, %17, %18, %19, %20, %21, %22, %23}, %24, %25, p, 1, 1, 0, 1;\n}\n"
        : "+f"(d[0]), "+f"(d[1]), "+f"(d[2]), "+f"(d[3]), "+f"(d[4]), "+f"(d[5]), "+f"(d[6]), "+f"(d[7]), "+f"(d[8]), "+f"(d[9]), "+f"(d[10]), "+f"(d[11]), "+f"(d[12]), "+f"(d[13]), "+f"(d[14]), "+f"(d[15]), "+f"(d[16]), "+f"(d[17]), "+f"(d[18]), "+f"(d[19]), "+f"(d[20]), "+f"(d[21]), "+f"(d[22]), "+f"(d[23])
        : "l"(da), "l"(db), "r"(scale_d));
}
__device__ __forceinline__ void wgmma_ss_n80(float (&d)[40], uint64_t da, uint64_t db, int scale_d) {
    asm volatile("{\n.reg .pred p;\nsetp.ne.b32 p, %42, 0;\n"
        "wgmma.mma_async.sync.aligned.m64n80k16.f32.bf16.bf16 {%0, %1, %2, %3, %4, %5, %6, %7, %8, %9, %10, %11, %12, %13, %14, %15, %16, %17, %18, %19, %20, %21, %22, %23, %24, %25, %26, %27, %28, %29, %30, %31, %32, %33, %34, %35, %36, %37, %38, %39}, %40, %41, p, 1, 1, 0, 1;\n}\n"
        : "+f"(d[0]), "+f"(d[1]), "+f"(d[2]), "+f"(d[3]), "+f"(d[4]), "+f"(d[5]), "+f"(d[6]), "+f"(d[7]), "+f"(d[8]), "+f"(d[9]), "+f"(d[10]), "+f"(d[11]), "+f"(d[12]), "+f"(d[13]), "+f"(d[14]), "+f"(d[15]), "+f"(d[16]), "+f"(d[17]), "+f"(d[18]), "+f"(d[19]), "+f"(d[20]), "+f"(d[21]), "+f"(d[22]), "+f"(d[23]), "+f"(d[24]), "+f"(d[25]), "+f"(d[26]), "+f"(d[27]), "+f"(d[28]), "+f"(d[29]), "+f"(d[30]), "+f"(d[31]), "+f"(d[32]), "+f"(d[33]), "+f"(d[34]), "+f"(d[35]), "+f"(d[36]), "+f"(d[37]), "+f"(d[38]), "+f"(d[39])
        : "l"(da), "l"(db), "r"(scale_d));
}
__device__ __forceinline__ void wgmma_ss_n160(float (&d)[80], uint64_t da, uint64_t db, int scale_d) {
    asm volatile("{\n.reg .pred p;\nsetp.ne.b32 p, %82, 0;\n"
        "wgmma.mma_async.sync.aligned.m64n160k16.f32.bf16.bf16 {%0, %1, %2, %3, %4, %5, %6, %7, %8, %9, %10, %11, %12, %13, %14, %15, %16, %17, %18, %19, %20, %21, %22, %23, %24, %25, %26, %27, %28, %29, %30, %31, %32, %33, %34, %35, %36, %37, %38, %39, %40, %41, %42, %43, %44, %45, %46, %47, %48, %49, %50, %51, %52, %53, %54, %55, %56, %57, %58, %59, %60, %61, %62, %63, %64, %65, %66, %67, %68, %69, %70, %71, %72, %73, %74, %75, %76, %77, %78, %79}, %80, %81, p, 1, 1, 0, 1;\n}\n"
        : "+f"(d[0]), "+f"(d[1]), "+f"(d[2]), "+f"(d[3]), "+f"(d[4]), "+f"(d[5]), "+f"(d[6]), "+f"(d[7]), "+f"(d[8]), "+f"(d[9]), "+f"(d[10]), "+f"(d[11]), "+f"(d[12]), "+f"(d[13]), "+f"(d[14]), "+f"(d[15]), "+f"(d[16]), "+f"(d[17]), "+f"(d[18]), "+f"(d[19]), "+f"(d[20]), "+f"(d[21]), "+f"(d[22]), "+f"(d[23]), "+f"(d[24]), "+f"(d[25]), "+f"(d[26]), "+f"(d[27]), "+f"(d[28]), "+f"(d[29]), "+f"(d[30]), "+f"(d[31]), "+f"(d[32]), "+f"(d[33]), "+f"(d[34]), "+f"(d[35]), "+f"(d[36]), "+f"(d[37]), "+f"(d[38]), "+f"(d[39]), "+f"(d[40]), "+f"(d[41]), "+f"(d[42]), "+f"(d[43]), "+f"(d[44]), "+f"(d[45]), "+f"(d[46]), "+f"(d[47]), "+f"(d[48]), "+f"(d[49]), "+f"(d[50]), "+f"(d[51]), "+f"(d[52]), "+f"(d[53]), "+f"(d[54]), "+f"(d[55]), "+f"(d[56]), "+f"(d[57]), "+f"(d[58]), "+f"(d[59]), "+f"(d[60]), "+f"(d[61]), "+f"(d[62]), "+f"(d[63]), "+f"(d[64]), "+f"(d[65]), "+f"(d[66]), "+f"(d[67]), "+f"(d[68]), "+f"(d[69]), "+f"(d[70]), "+f"(d[71]), "+f"(d[72]), "+f"(d[73]), "+f"(d[74]), "+f"(d[75]), "+f"(d[76]), "+f"(d[77]), "+f"(d[78]), "+f"(d[79])
        : "l"(da), "l"(db), "r"(scale_d));
}
__device__ __forceinline__ void wgmma_ss_n256(float (&d)[128], uint64_t da, uint64_t db, int scale_d) {
    asm volatile("{\n.reg .pred p;\nsetp.ne.b32 p, %130, 0;\n"
        "wgmma.mma_async.sync.aligned.m64n256k16.f32.bf16.bf16 {%0, %1, %2, %3, %4, %5, %6, %7, %8, %9, %10, %11, %12, %13, %14, %15, %16, %17, %18, %19, %20, %21, %22, %23, %24, %25, %26, %27, %28, %29, %30, %31, %32, %33, %34, %35, %36, %37, %38, %39, %40, %41, %42, %43, %44, %45, %46, %47, %48, %49, %50, %51, %52, %53, %54, %55, %56, %57, %58, %59, %60, %61, %62, %63, %64, %65, %66, %67, %68, %69, %70, %71, %72, %73, %74, %75, %76, %77, %78, %79, %80, %81, %82, %83, %84, %85, %86, %87, %88, %89, %90, %91, %92, %93, %94, %95, %96, %97, %98, %99, %100, %101, %102, %103, %104, %105, %106, %107, %108, %109, %110, %111, %112, %113, %114, %115, %116, %117, %118, %119, %120, %121, %122, %123, %124, %125, %126, %127}, %128, %129, p, 1, 1, 0, 1;\n}\n"
        : "+f"(d[0]), "+f"(d[1]), "+f"(d[2]), "+f"(d[3]), "+f"(d[4]), "+f"(d[5]), "+f"(d[6]), "+f"(d[7]), "+f"(d[8]), "+f"(d[9]), "+f"(d[10]), "+f"(d[11]), "+f"(d[12]), "+f"(d[13]), "+f"(d[14]), "+f"(d[15]), "+f"(d[16]), "+f"(d[17]), "+f"(d[18]), "+f"(d[19]), "+f"(d[20]), "+f"(d[21]), "+f"(d[22]), "+f"(d[23]), "+f"(d[24]), "+f"(d[25]), "+f"(d[26]), "+f"(d[27]), "+f"(d[28]), "+f"(d[29]), "+f"(d[30]), "+f"(d[31]), "+f"(d[32]), "+f"(d[33]), "+f"(d[34]), "+f"(d[35]), "+f"(d[36]), "+f"(d[37]), "+f"(d[38]), "+f"(d[39]), "+f"(d[40]), "+f"(d[41]), "+f"(d[42]), "+f"(d[43]), "+f"(d[44]), "+f"(d[45]), "+f"(d[46]), "+f"(d[47]), "+f"(d[48]), "+f"(d[49]), "+f"(d[50]), "+f"(d[51]), "+f"(d[52]), "+f"(d[53]), "+f"(d[54]), "+f"(d[55]), "+f"(d[56]), "+f"(d[57]), "+f"(d[58]), "+f"(d[59]), "+f"(d[60]), "+f"(d[61]), "+f"(d[62]), "+f"(d[63]), "+f"(d[64]), "+f"(d[65]), "+f"(d[66]), "+f"(d[67]), "+f"(d[68]), "+f"(d[69]), "+f"(d[70]), "+f"(d[71]), "+f"(d[72]), "+f"(d[73]), "+f"(d[74]), "+f"(d[75]), "+f"(d[76]), "+f"(d[77]), "+f"(d[78]), "+f"(d[79]), "+f"(d[80]), "+f"(d[81]), "+f"(d[82]), "+f"(d[83]), "+f"(d[84]), "+f"(d[85]), "+f"(d[86]), "+f"(d[87]), "+f"(d[88]), "+f"(d[89]), "+f"(d[90]), "+f"(d[91]), "+f"(d[92]), "+f"(d[93]), "+f"(d[94]), "+f"(d[95]), "+f"(d[96]), "+f"(d[97]), "+f"(d[98]), "+f"(d[99]), "+f"(d[100]), "+f"(d[101]), "+f"(d[102]), "+f"(d[103]), "+f"(d[104]), "+f"(d[105]), "+f"(d[106]), "+f"(d[107]), "+f"(d[108]), "+f"(d[109]), "+f"(d[110]), "+f"(d[111]), "+f"(d[112]), "+f"(d[113]), "+f"(d[114]), "+f"(d[115]), "+f"(d[116]), "+f"(d[117]), "+f"(d[118]), "+f"(d[119]), "+f"(d[120]), "+f"(d[121]), "+f"(d[122]), "+f"(d[123]), "+f"(d[124]), "+f"(d[125]), "+f"(d[126]), "+f"(d[127])
        : "l"(da), "l"(db), "r"(scale_d));
}

__device__ __forceinline__ uint32_t smem_u32(const void* p) { return (uint32_t)__cvta_generic_to_shared(p); }
__device__ __forceinline__ void wg_fence() { asm volatile("wgmma.fence.sync.aligned;" ::: "memory"); }
__device__ __forceinline__ void wg_commit() { asm volatile("wgmma.commit_group.sync.aligned;" ::: "memory"); }
template <int N> __device__ __forceinline__ void wg_wait() { asm volatile("wgmma.wait_group.sync.aligned %0;" :: "n"(N) : "memory"); }
__device__ __forceinline__ uint64_t mkdesc(uint32_t addr, uint32_t lbo, uint32_t sbo, uint32_t mode) {
    return (uint64_t)((addr & 0x3FFFF) >> 4) | ((uint64_t)(lbo >> 4) << 16) | ((uint64_t)(sbo >> 4) << 32) | ((uint64_t)mode << 62);
}
__device__ __forceinline__ void mbar_init(uint32_t bar, int cnt) { asm volatile("mbarrier.init.shared::cta.b64 [%0], %1;" :: "r"(bar), "r"(cnt) : "memory"); }
__device__ __forceinline__ void mbar_expect_tx(uint32_t bar, uint32_t bytes) { asm volatile("mbarrier.arrive.expect_tx.shared::cta.b64 _, [%0], %1;" :: "r"(bar), "r"(bytes) : "memory"); }
__device__ __forceinline__ void mbar_arrive(uint32_t bar) { asm volatile("mbarrier.arrive.shared::cta.b64 _, [%0];" :: "r"(bar) : "memory"); }
__device__ __forceinline__ bool mbar_try(uint32_t bar, uint32_t parity) {
    uint32_t ok;
    asm volatile("{\n.reg .pred p;\nmbarrier.try_wait.parity.shared::cta.b64 p, [%1], %2;\nselp.b32 %0, 1, 0, p;\n}" : "=r"(ok) : "r"(bar), "r"(parity) : "memory");
    return ok != 0;
}
__device__ __forceinline__ void mbar_wait(uint32_t bar, uint32_t parity) {
    if (!mbar_try(bar, parity)) {
        const uint32_t t0 = (uint32_t)clock();
        while (!mbar_try(bar, parity)) { if ((uint32_t)clock() - t0 > 2000000000u) __trap(); }
    }
}
__device__ __forceinline__ uint32_t ld_acquire(const unsigned* p) { uint32_t v; asm volatile("ld.acquire.gpu.global.u32 %0, [%1];" : "=r"(v) : "l"(p) : "memory"); return v; }
__device__ __forceinline__ void red_release(unsigned* p) { asm volatile("red.release.gpu.global.add.u32 [%0], 1;" :: "l"(p) : "memory"); }
__device__ __forceinline__ void flag_wait(const unsigned* p, uint32_t target) {
    const uint32_t t0 = (uint32_t)clock();
    while ((int)(ld_acquire(p) - target) < 0) { if ((uint32_t)clock() - t0 > 2000000000u) __trap(); }
}
__device__ __forceinline__ void fence_async_all() { asm volatile("fence.proxy.async;" ::: "memory"); }
__device__ __forceinline__ void fence_async_smem() { asm volatile("fence.proxy.async.shared::cta;" ::: "memory"); }
__device__ __forceinline__ void bar_sync(int id, int n) { asm volatile("bar.sync %0, %1;" :: "r"(id), "r"(n) : "memory"); }
__device__ __forceinline__ void bulk_load(uint32_t dst, const void* src, uint32_t bytes, uint32_t bar) {
    asm volatile("cp.async.bulk.shared::cluster.global.mbarrier::complete_tx::bytes [%0], [%1], %2, [%3];" :: "r"(dst), "l"(src), "r"(bytes), "r"(bar) : "memory");
}
__device__ __forceinline__ void bulk_store(void* dst, uint32_t src, uint32_t bytes) {
    asm volatile("cp.async.bulk.global.shared::cta.bulk_group [%0], [%1], %2;" :: "l"(dst), "r"(src), "r"(bytes) : "memory");
}
__device__ __forceinline__ void bulk_commit_wait() {
    asm volatile("cp.async.bulk.commit_group;" ::: "memory");
    asm volatile("cp.async.bulk.wait_group 0;" ::: "memory");
}
__device__ __forceinline__ void l2_prefetch(const void* src, uint32_t bytes) { asm volatile("cp.async.bulk.prefetch.L2.global [%0], %1;" :: "l"(src), "r"(bytes) : "memory"); }
__device__ __forceinline__ void tma2d(uint32_t dst, const CUtensorMap* tm, int c0, int c1, uint32_t bar) {
    asm volatile("cp.async.bulk.tensor.2d.shared::cluster.global.mbarrier::complete_tx::bytes [%0], [%1, {%3, %4}], [%2];"
                 :: "r"(dst), "l"(tm), "r"(bar), "r"(c0), "r"(c1) : "memory");
}
__device__ __forceinline__ void tma3d(uint32_t dst, const CUtensorMap* tm, int c0, int c1, int c2, uint32_t bar) {
    asm volatile("cp.async.bulk.tensor.3d.shared::cluster.global.mbarrier::complete_tx::bytes [%0], [%1, {%3, %4, %5}], [%2];"
                 :: "r"(dst), "l"(tm), "r"(bar), "r"(c0), "r"(c1), "r"(c2) : "memory");
}
__device__ __forceinline__ void sts32(uint32_t a, uint32_t v) { asm volatile("st.shared.b32 [%0], %1;" :: "r"(a), "r"(v) : "memory"); }
__device__ __forceinline__ uint32_t lds32(uint32_t a) { uint32_t v; asm volatile("ld.shared.b32 %0, [%1];" : "=r"(v) : "r"(a) : "memory"); return v; }
__device__ __forceinline__ void sts128(uint32_t a, uint32_t x, uint32_t y, uint32_t z, uint32_t w) { asm volatile("st.shared.v4.b32 [%0], {%1, %2, %3, %4};" :: "r"(a), "r"(x), "r"(y), "r"(z), "r"(w) : "memory"); }
__device__ __forceinline__ void stsm4(uint32_t a, uint32_t x, uint32_t y, uint32_t z, uint32_t w) { asm volatile("stmatrix.sync.aligned.m8n8.x4.shared.b16 [%0], {%1, %2, %3, %4};" :: "r"(a), "r"(x), "r"(y), "r"(z), "r"(w) : "memory"); }
__device__ __forceinline__ void ldsm4(uint32_t a, uint32_t& x, uint32_t& y, uint32_t& z, uint32_t& w) { asm volatile("ldmatrix.sync.aligned.m8n8.x4.shared.b16 {%0, %1, %2, %3}, [%4];" : "=r"(x), "=r"(y), "=r"(z), "=r"(w) : "r"(a) : "memory"); }
__device__ __forceinline__ float ex2(float x) { float y; asm("ex2.approx.ftz.f32 %0, %1;" : "=f"(y) : "f"(x)); return y; }
__device__ __forceinline__ float rcp(float x) { float y; asm("rcp.approx.ftz.f32 %0, %1;" : "=f"(y) : "f"(x)); return y; }
__device__ __forceinline__ uint32_t pack_bf16(float lo, float hi) { uint32_t r; asm("cvt.rn.bf16x2.f32 %0, %1, %2;" : "=r"(r) : "f"(hi), "f"(lo)); return r; }
__device__ __forceinline__ float bf_lo(uint32_t v) { return __uint_as_float(v << 16); }
__device__ __forceinline__ float bf_hi(uint32_t v) { return __uint_as_float(v & 0xffff0000u); }
__device__ __forceinline__ float bf_round(float x) { return bf_lo(pack_bf16(x, 0.f)); }
__device__ __forceinline__ uint32_t bf2_sub(uint32_t a, uint32_t b) { uint32_t r; asm("sub.rn.bf16x2 %0, %1, %2;" : "=r"(r) : "r"(a), "r"(b)); return r; }
__device__ __forceinline__ uint32_t bf2_add(uint32_t a, uint32_t b) { uint32_t r; asm("add.rn.bf16x2 %0, %1, %2;" : "=r"(r) : "r"(a), "r"(b)); return r; }
__device__ __forceinline__ uint32_t bf2_mul(uint32_t a, uint32_t b) { uint32_t r; asm("mul.rn.bf16x2 %0, %1, %2;" : "=r"(r) : "r"(a), "r"(b)); return r; }

__device__ __forceinline__ float ex2_poly(float x) {
    float u;
    asm("fma.rn.sat.f32 %0, %1, %2, %3;" : "=f"(u) : "f"(x), "f"(1.0f / 254.0f), "f"(126.0f / 254.0f));
    const float MG = 12582912.0f - 126.0f;
    float t = fmaf(u, 254.0f, MG);
    float n2 = MG - t;
    float f = fmaf(u, 254.0f, n2);
    float p;
    p = fmaf(0.0013276472454890609f, f, 0.009675540961325169f);
    p = fmaf(p, f, 0.05550713092088699f);
    p = fmaf(p, f, 0.24022120237350464f);
    p = fmaf(p, f, 0.6931469440460205f);
    p = fmaf(p, f, 1.0000001192092896f);
    return __uint_as_float(__float_as_uint(p) + (__float_as_uint(t) << 23));
}
template <int C>
__device__ __forceinline__ void chunk(const float (&s)[32], uint32_t (&p)[16]) {
#pragma unroll
    for (int i = 4 * C; i < 4 * C + 4; i++) {
        float a = ((PMASK >> (2 * i)) & 1) ? ex2_poly(s[2 * i]) : ex2(s[2 * i]);
        float b = ((PMASK >> (2 * i + 1)) & 1) ? ex2_poly(s[2 * i + 1]) : ex2(s[2 * i + 1]);
        p[i] = pack_bf16(a, b);
    }
}
#define PV(o, p, C, d) wgmma_rs_n24_t1(o, p[4 * C], p[4 * C + 1], p[4 * C + 2], p[4 * C + 3], (d) + 96 * C, 1)
#define QK0(s, q, d) wgmma_rs_n64_t0(s, q[0], q[1], q[2], q[3], d, 0)
#define QK1(s, q, d) wgmma_rs_n64_t0(s, q[4], q[5], 0u, 0u, (d) + 16, 1)

__device__ __noinline__ void attn_exact_row(uint32_t qo, int row, int col0) {
    float q[20], o[20];
#pragma unroll
    for (int d = 0; d < 20; d += 2) {
        const int col = col0 + d;
        uint32_t v = lds32(qo + (col >> 3) * 1024 + (row >> 3) * 128 + (row & 7) * 16 + (col & 7) * 2);
        q[d] = bf_lo(v); q[d + 1] = bf_hi(v); o[d] = 0.f; o[d + 1] = 0.f;
    }
    float m = -INFINITY, l = 0.f;
    const uint32_t* kv = (const uint32_t*)g_kv;
#pragma unroll 1
    for (int key = 0; key < 2048; key++) {
        const uint32_t* p = kv + (key >> 3) * 192 + (key & 7) * 4;
        float s = 0.f;
#pragma unroll
        for (int d = 0; d < 20; d += 2) {
            uint32_t v = __ldcg(p + (d >> 3) * 32 + ((d & 7) >> 1));
            s = fmaf(q[d], bf_lo(v), s); s = fmaf(q[d + 1], bf_hi(v), s);
        }
        const float mn = fmaxf(m, s);
        const float sc = exp2f(m - mn), e = exp2f(s - mn);
        m = mn; l = l * sc + e;
#pragma unroll
        for (int d = 0; d < 20; d += 2) {
            uint32_t v = __ldcg(p + 96 + (d >> 3) * 32 + ((d & 7) >> 1));
            o[d] = fmaf(e, bf_lo(v), o[d] * sc); o[d + 1] = fmaf(e, bf_hi(v), o[d + 1] * sc);
        }
    }
    const float il = 1.0f / l;
#pragma unroll
    for (int d = 0; d < 20; d += 2) {
        const int col = col0 + d;
        sts32(qo + (col >> 3) * 1024 + (row >> 3) * 128 + (row & 7) * 16 + (col & 7) * 2, pack_bf16(o[d] * il, o[d + 1] * il));
    }
}

struct Params {
    const __nv_bfloat16 *x, *wq, *wk, *wv, *wo, *wg, *wu, *wd;
    __nv_bfloat16* out;
};

__device__ __forceinline__ void issue_stage(int s, uint32_t sb, const CUtensorMap* tq, const CUtensorMap* tg, const CUtensorMap* tu,
                                            const CUtensorMap* td, int rb, int cb, bool withA) {
    const int sl = s % 3;
    const uint32_t slot = sb + RING_OFF + sl * 32768, bar = sb + BAR_OFF + (B_RING + sl) * 8;
    if (s < 5) {
        mbar_expect_tx(bar, 24576);
#pragma unroll
        for (int h = 0; h < 2; h++)
#pragma unroll
            for (int g = 0; g < 3; g++) tma2d(slot + h * 12288 + g * 4096, tq, cb * 160 + 80 + 32 * g, (2 * s + h) * 64, bar);
    } else if (s < 35) {
        const int jj = (s - 5) / 10, kc = (s - 5) % 10;
        mbar_expect_tx(bar, 32768);
        tma3d(slot, tg, 0, kc * 64, cb * 6 + jj * 2, bar);
        tma3d(slot + 16384, tu, 0, kc * 64, cb * 6 + jj * 2, bar);
    } else if (s < 59) {
        const int kc = s - 35;
        mbar_expect_tx(bar, 28672);
        tma3d(slot + 8192, td, 0, kc * 64, cb * 5, bar);
        if (withA) bulk_load(slot, (const char*)g_h + (size_t)(rb * 24 + kc) * 8192, 8192, bar);
    }
}

__global__ void __launch_bounds__(384, 1)
fused_kernel(const __grid_constant__ CUtensorMap tm_wq, const __grid_constant__ CUtensorMap tm_wg, const __grid_constant__ CUtensorMap tm_wu,
             const __grid_constant__ CUtensorMap tm_wd, const __grid_constant__ CUtensorMap tm_wo, const Params P) {
    extern __shared__ __align__(1024) char smem_raw[];
    const uint32_t sb = smem_u32(smem_raw);
    const uint32_t bars = sb + BAR_OFF;
    const int tid = threadIdx.x, wg = tid >> 7, warp = (tid >> 5) & 3, lane = tid & 31;
    const int r = lane >> 2, c = lane & 3;
    const int bid = blockIdx.x;
    const int rb = ((bid >> 3) << 1) | (bid & 1), cb = (bid >> 1) & 3;
    constexpr float QSCALE = 0.22360679774997896f * 1.4426950408889634f;

    if (wg < 2) {
        const int row = (wg * 4 + warp) * 8 + (((r & 1) << 2) | (r >> 1));
        const uint4* xr = (const uint4*)(P.x + (size_t)(rb * 64 + row) * 640) + c;
        uint4 v[20];
#pragma unroll
        for (int t = 0; t < 20; t++) v[t] = __ldg(xr + 4 * t);
        float s0 = 0.f, s1 = 0.f, s2 = 0.f, s3 = 0.f;
#pragma unroll
        for (int t = 0; t < 20; t++) {
            s0 += bf_lo(v[t].x); s1 += bf_hi(v[t].x); s2 += bf_lo(v[t].y); s3 += bf_hi(v[t].y);
            s0 += bf_lo(v[t].z); s1 += bf_hi(v[t].z); s2 += bf_lo(v[t].w); s3 += bf_hi(v[t].w);
        }
        float s = (s0 + s1) + (s2 + s3);
        s += __shfl_xor_sync(~0u, s, 1); s += __shfl_xor_sync(~0u, s, 2);
        const float mean = s * (1.0f / 640.0f);
        s0 = s1 = s2 = s3 = 0.f;
#pragma unroll
        for (int t = 0; t < 20; t++) {
            float a;
            a = bf_lo(v[t].x) - mean; s0 = fmaf(a, a, s0); a = bf_hi(v[t].x) - mean; s1 = fmaf(a, a, s1);
            a = bf_lo(v[t].y) - mean; s2 = fmaf(a, a, s2); a = bf_hi(v[t].y) - mean; s3 = fmaf(a, a, s3);
            a = bf_lo(v[t].z) - mean; s0 = fmaf(a, a, s0); a = bf_hi(v[t].z) - mean; s1 = fmaf(a, a, s1);
            a = bf_lo(v[t].w) - mean; s2 = fmaf(a, a, s2); a = bf_hi(v[t].w) - mean; s3 = fmaf(a, a, s3);
        }
        s = (s0 + s1) + (s2 + s3);
        s += __shfl_xor_sync(~0u, s, 1); s += __shfl_xor_sync(~0u, s, 2);
        const float var = bf_round(s * (1.0f / 640.0f));
        const float rinv = 1.0f / bf_round(sqrtf(bf_round(var + 1e-5f)));
        const uint32_t m2 = pack_bf16(mean, mean);
        const uint32_t xa = sb + XN_OFF + row * 128;
#pragma unroll
        for (int t = 0; t < 20; t++) {
            uint32_t d0 = bf2_sub(v[t].x, m2), d1 = bf2_sub(v[t].y, m2), d2 = bf2_sub(v[t].z, m2), d3 = bf2_sub(v[t].w, m2);
            const int cu = (t & 1) * 4 + c;
            sts128(xa + (t >> 1) * 8192 + ((cu ^ (row & 7)) << 4),
                   pack_bf16(bf_lo(d0) * rinv, bf_hi(d0) * rinv), pack_bf16(bf_lo(d1) * rinv, bf_hi(d1) * rinv),
                   pack_bf16(bf_lo(d2) * rinv, bf_hi(d2) * rinv), pack_bf16(bf_lo(d3) * rinv, bf_hi(d3) * rinv));
        }
        fence_async_smem();
        PROF(0 + wg * 8);
        __syncthreads();

        uint32_t qa[6], qb[6];
        {
            float d[24];
            mbar_wait(bars + B_SLAB * 8, 0);
            const uint64_t dA = mkdesc(sb + XN_OFF, 16, 1024, 1);
            const uint64_t dB = mkdesc(sb + RING_OFF + wg * 4096, 4096, 512, 2);
            wg_fence();
#pragma unroll
            for (int kc = 0; kc < 10; kc++) {
#pragma unroll
                for (int k = 0; k < 4; k++) wgmma_ss_n48(d, dA + kc * 512 + k * 2, dB + kc * 768 + k * 64, (kc | k) != 0);
            }
            wg_commit();
            wg_wait<0>();
#pragma unroll
            for (int i = 0; i < 24; i++) asm volatile("" : "+f"(d[i]) :: "memory");
            if (lane == 0) mbar_arrive(bars + B_SLABFREE * 8);
            uint32_t p0[5], p1[5];
#pragma unroll
            for (int i = 0; i < 5; i++) {
                p0[i] = pack_bf16((wg ? d[4 * i + 4] : d[4 * i]) * QSCALE, (wg ? d[4 * i + 5] : d[4 * i + 1]) * QSCALE);
                p1[i] = pack_bf16((wg ? d[4 * i + 6] : d[4 * i + 2]) * QSCALE, (wg ? d[4 * i + 7] : d[4 * i + 3]) * QSCALE);
            }
            qa[0] = p0[0]; qa[1] = p1[0]; qa[2] = p0[1]; qa[3] = p1[1];
            qa[4] = c < 2 ? p0[2] : 0u; qa[5] = c < 2 ? p1[2] : 0u;
            qb[0] = __shfl_xor_sync(~0u, c >= 2 ? p0[2] : p0[3], 2); qb[1] = __shfl_xor_sync(~0u, c >= 2 ? p1[2] : p1[3], 2);
            qb[2] = __shfl_xor_sync(~0u, c >= 2 ? p0[3] : p0[4], 2); qb[3] = __shfl_xor_sync(~0u, c >= 2 ? p1[3] : p1[4], 2);
            qb[4] = __shfl_xor_sync(~0u, c >= 2 ? p0[4] : 0u, 2); qb[5] = __shfl_xor_sync(~0u, c >= 2 ? p1[4] : 0u, 2);
        }
        PROF(1 + wg * 8);

        const uint64_t dK0 = mkdesc(sb + KVR_OFF, 128, 768, 0);
        const uint64_t dV0 = mkdesc(sb + KVR_OFF + 384, 768, 128, 0);
        const uint32_t qo_a = sb + QO_OFF + wg * 5120 + warp * 256 + r * 16 + c * 4;
        const uint32_t qo_b = sb + QO_OFF + wg * 5120 + warp * 256 + r * 16 + (c < 2 ? 2048 + 8 + c * 4 : 3072 + (c - 2) * 4);
#pragma unroll 1
        for (int pass = 0; pass < 2; pass++) {
            float sa[32], sbb[32], oa[12], ob[12];
            uint32_t pa[16], pb[16];
#pragma unroll
            for (int i = 0; i < 12; i++) { oa[i] = 0.f; ob[i] = 0.f; }
            mbar_wait(bars + B_KVFULL * 8, 0);
            wg_fence();
            QK0(sa, qa, dK0); QK1(sa, qa, dK0); QK0(sbb, qb, dK0); QK1(sbb, qb, dK0);
            wg_commit(); wg_wait<0>();
#pragma unroll
            for (int i = 0; i < 32; i++) asm volatile("" : "+f"(sa[i]), "+f"(sbb[i]) :: "memory");
            {
                float m0 = -INFINITY, m1 = -INFINITY, m2 = -INFINITY, m3 = -INFINITY;
#pragma unroll
                for (int j = 0; j < 8; j++) {
                    m0 = fmaxf(m0, fmaxf(sa[4 * j], sa[4 * j + 1])); m1 = fmaxf(m1, fmaxf(sa[4 * j + 2], sa[4 * j + 3]));
                    m2 = fmaxf(m2, fmaxf(sbb[4 * j], sbb[4 * j + 1])); m3 = fmaxf(m3, fmaxf(sbb[4 * j + 2], sbb[4 * j + 3]));
                }
#pragma unroll
                for (int o = 1; o < 4; o <<= 1) {
                    m0 = fmaxf(m0, __shfl_xor_sync(~0u, m0, o)); m1 = fmaxf(m1, __shfl_xor_sync(~0u, m1, o));
                    m2 = fmaxf(m2, __shfl_xor_sync(~0u, m2, o)); m3 = fmaxf(m3, __shfl_xor_sync(~0u, m3, o));
                }
                if (c == 2) {
                    qa[4] = pack_bf16(-(m0 + 80.f), 0.f); qa[5] = pack_bf16(-(m1 + 80.f), 0.f);
                    qb[4] = pack_bf16(-(m2 + 80.f), 0.f); qb[5] = pack_bf16(-(m3 + 80.f), 0.f);
                }
            }
            wg_fence();
            QK0(sa, qa, dK0); QK1(sa, qa, dK0);
            wg_commit(); wg_wait<0>();
            pb[12] = pb[13] = pb[14] = pb[15] = 0u;
            uint64_t dVp = dV0;
#pragma unroll 1
            for (int g = pass * 32; g < pass * 32 + 32; g++) {
                const uint64_t dK = dK0 + (g & 3) * 384, dV = dV0 + (g & 3) * 384;
                const int gn = g < 63 ? g + 1 : g;
                const uint64_t dKn = dK0 + (gn & 3) * 384;
                wg_fence(); PV(ob, pb, 3, dVp); wg_commit();
                chunk<0>(sa, pa);
                wg_fence(); QK0(sbb, qb, dK); PV(oa, pa, 0, dV); wg_commit();
                chunk<1>(sa, pa);
                wg_fence(); QK1(sbb, qb, dK); PV(oa, pa, 1, dV); wg_commit();
                chunk<2>(sa, pa);
                wg_fence(); PV(oa, pa, 2, dV); wg_commit();
                chunk<3>(sa, pa);
                wg_wait<1>();
                uint32_t old = 0;
                const bool rel = (lane == 0) && (g >= 1) && (g < 61);
                if (rel) asm volatile("atom.acq_rel.cta.shared.add.u32 %0, [%1], 1;" : "=r"(old) : "r"(sb + KVCNT_OFF + ((g - 1) & 3) * 4) : "memory");
                wg_fence(); PV(oa, pa, 3, dV); wg_commit();
                chunk<0>(sbb, pb);
                if (rel && (old & 7) == 7) {
                    mbar_wait(bars + B_KVALL * 8, 0);
                    fence_async_all();
                    const uint32_t fb = bars + (B_KVFULL + ((g - 1) & 3)) * 8;
                    mbar_expect_tx(fb, 6144);
                    bulk_load(sb + KVR_OFF + ((g - 1) & 3) * 6144, (const char*)g_kv + ((rb + g + 3) & 31) * 6144, 6144, fb);
                }
                mbar_wait(bars + (B_KVFULL + (gn & 3)) * 8, (gn >> 2) & 1);
                wg_fence(); QK0(sa, qa, dKn); PV(ob, pb, 0, dV); wg_commit();
                chunk<1>(sbb, pb);
                wg_fence(); QK1(sa, qa, dKn); PV(ob, pb, 1, dV); wg_commit();
                chunk<2>(sbb, pb);
                wg_fence(); PV(ob, pb, 2, dV); wg_commit();
                chunk<3>(sbb, pb);
                wg_wait<1>();
                dVp = dV;
            }
            wg_fence(); PV(ob, pb, 3, dVp); wg_commit();
            wg_wait<0>();
#pragma unroll
            for (int i = 0; i < 12; i++) asm volatile("" : "+f"(oa[i]), "+f"(ob[i]) :: "memory");
            PROF(2 + pass * 2 + wg * 8);
            uint32_t na[6], nb[6];
            if (pass == 0) {
                mbar_wait(bars + B_Q2 * 8, 0);
                na[0] = lds32(qo_a); na[1] = lds32(qo_a + 128); na[2] = lds32(qo_a + 1024); na[3] = lds32(qo_a + 1152);
                na[4] = c < 2 ? lds32(qo_a + 2048) : 0u; na[5] = c < 2 ? lds32(qo_a + 2176) : 0u;
                nb[0] = lds32(qo_b); nb[1] = lds32(qo_b + 128); nb[2] = lds32(qo_b + 1024); nb[3] = lds32(qo_b + 1152);
                nb[4] = c < 2 ? lds32(qo_b + 2048) : 0u; nb[5] = c < 2 ? lds32(qo_b + 2176) : 0u;
                __syncwarp();
            } else {
                mbar_wait(bars + B_QOFREE * 8, 0);
#pragma unroll
                for (int i = 0; i < 6; i++) { na[i] = 0u; nb[i] = 0u; }
            }
            const int src = (lane & ~3) | 2;
            const float l0 = __shfl_sync(~0u, oa[8], src), l1 = __shfl_sync(~0u, oa[10], src);
            const float l2 = __shfl_sync(~0u, ob[8], src), l3 = __shfl_sync(~0u, ob[10], src);
            const float LO = 8.0779e-28f  , HI = 1.0e37f;
            bool ok = (l0 >= LO) && (l0 <= HI) && (l1 >= LO) && (l1 <= HI) && (l2 >= LO) && (l2 <= HI) && (l3 >= LO) && (l3 <= HI);
            float amax = 0.f;
#pragma unroll
            for (int i = 0; i < 12; i++) amax = amax + fabsf(oa[i]) * 0.03125f + fabsf(ob[i]) * 0.03125f;
            ok = ok && (amax <= 3.0e38f);
            if (__all_sync(~0u, ok)) {
                const float i0 = 1.0f / l0, i1 = 1.0f / l1, i2 = 1.0f / l2, i3 = 1.0f / l3;
                sts32(qo_a, pack_bf16(oa[0] * i0, oa[1] * i0)); sts32(qo_a + 128, pack_bf16(oa[2] * i1, oa[3] * i1));
                sts32(qo_a + 1024, pack_bf16(oa[4] * i0, oa[5] * i0)); sts32(qo_a + 1152, pack_bf16(oa[6] * i1, oa[7] * i1));
                sts32(qo_b, pack_bf16(ob[0] * i2, ob[1] * i2)); sts32(qo_b + 128, pack_bf16(ob[2] * i3, ob[3] * i3));
                sts32(qo_b + 1024, pack_bf16(ob[4] * i2, ob[5] * i2)); sts32(qo_b + 1152, pack_bf16(ob[6] * i3, ob[7] * i3));
                if (c < 2) {
                    sts32(qo_a + 2048, pack_bf16(oa[8] * i0, oa[9] * i0)); sts32(qo_a + 2176, pack_bf16(oa[10] * i1, oa[11] * i1));
                    sts32(qo_b + 2048, pack_bf16(ob[8] * i2, ob[9] * i2)); sts32(qo_b + 2176, pack_bf16(ob[10] * i3, ob[11] * i3));
                }
            } else {
                sts32(qo_a, qa[0]); sts32(qo_a + 128, qa[1]); sts32(qo_a + 1024, qa[2]); sts32(qo_a + 1152, qa[3]);
                sts32(qo_b, qb[0]); sts32(qo_b + 128, qb[1]); sts32(qo_b + 1024, qb[2]); sts32(qo_b + 1152, qb[3]);
                if (c < 2) { sts32(qo_a + 2048, qa[4]); sts32(qo_a + 2176, qa[5]); sts32(qo_b + 2048, qb[4]); sts32(qo_b + 2176, qb[5]); }
                __syncwarp();
                mbar_wait(bars + B_KVALL * 8, 0);
                attn_exact_row(sb + QO_OFF, warp * 16 + (lane & 15), wg * 40 + (lane >> 4) * 20);
            }
            fence_async_smem();
            __syncwarp();
            if (lane == 0) mbar_arrive(bars + B_OREADY * 8);
#pragma unroll
            for (int i = 0; i < 6; i++) { qa[i] = na[i]; qb[i] = nb[i]; }
            PROF(3 + pass * 2 + wg * 8);
        }
    } else {
        const int t = tid - 256;
        uint32_t epoch = 0;
        if (t == 0) {
            mbar_init(bars + B_SLAB * 8, 1); mbar_init(bars + B_SLABFREE * 8, 8);
            for (int i = 0; i < 4; i++) { mbar_init(bars + (B_KVFULL + i) * 8, 1); mbar_init(bars + (B_WO + i) * 8, 1); sts32(sb + KVCNT_OFF + i * 4, 0u); }
            mbar_init(bars + B_KVALL * 8, 1);
            for (int i = 0; i < 3; i++) mbar_init(bars + (B_RING + i) * 8, 1);
            mbar_init(bars + B_Q2 * 8, 4); mbar_init(bars + B_OREADY * 8, 8); mbar_init(bars + B_QOFREE * 8, 1);
            mbar_init(bars + B_OBLOB * 8, 1); mbar_init(bars + B_XT * 8, 1);
            asm volatile("fence.mbarrier_init.release.cluster;" ::: "memory");
            fence_async_smem();
            mbar_expect_tx(bars + B_SLAB * 8, 122880);
            for (int kc = 0; kc < 10; kc++)
#pragma unroll
                for (int g = 0; g < 3; g++) tma2d(sb + RING_OFF + kc * 12288 + g * 4096, &tm_wq, cb * 160 + 32 * g, kc * 64, bars + B_SLAB * 8);
        }
        if (warp == 0) epoch = *(volatile unsigned*)&g_epoch[bid] + 1u;
        {
            const uint32_t* wsrc = (const uint32_t*)((cb < 2 ? P.wk : P.wv) + (cb & 1) * 10);
            uint32_t w[5][5];
#pragma unroll
            for (int i = 0; i < 5; i++)
#pragma unroll
                for (int j = 0; j < 5; j++) w[i][j] = __ldg(wsrc + (t + 128 * i) * 10 + j);
#pragma unroll
            for (int i = 0; i < 5; i++) {
                const int k = t + 128 * i;
                const uint32_t a = sb + KVR_OFF + (k >> 3) * 256 + (k & 7) * 16;
                sts128(a, w[i][0], w[i][1], w[i][2], w[i][3]);
                sts128(a + 128, w[i][4], 0u, 0u, 0u);
            }
        }
        fence_async_smem();
        PROF(16);
        __syncthreads();
        const uint64_t dXN = mkdesc(sb + XN_OFF, 16, 1024, 1);
        {
            float d[8];
            const uint64_t dB = mkdesc(sb + KVR_OFF, 256, 128, 0);
            wg_fence();
#pragma unroll
            for (int kc = 0; kc < 10; kc++) {
#pragma unroll
                for (int k = 0; k < 4; k++) wgmma_ss_n16(d, dXN + kc * 512 + k * 2, dB + kc * 128 + k * 32, (kc | k) != 0);
            }
            wg_commit();
            if (t == 32) {
                l2_prefetch((const char*)P.wq + bid * 6400, 6400);
                l2_prefetch((const char*)P.wg + bid * 15360, 15360);
                l2_prefetch((const char*)P.wu + bid * 15360, 15360);
                l2_prefetch((const char*)P.wd + bid * 15360, 15360);
                l2_prefetch((const char*)P.wo + bid * 6400, 6400);
            }
            wg_wait<0>();
#pragma unroll
            for (int i = 0; i < 8; i++) asm volatile("" : "+f"(d[i]) :: "memory");
            char* kvb = (char*)g_kv + rb * 6144 + warp * 1536 + (cb >> 1) * 384 + r * 16;
            const int d0 = (cb & 1) * 10 + 2 * c, d1 = d0 + 8;
            *(uint32_t*)(kvb + (d0 >> 3) * 128 + (d0 & 7) * 2) = pack_bf16(d[0], d[1]);
            *(uint32_t*)(kvb + 768 + (d0 >> 3) * 128 + (d0 & 7) * 2) = pack_bf16(d[2], d[3]);
            if (c == 0 || ((cb & 1) && c < 3)) {
                const uint32_t cst = c == 1 ? 0x00003F80u : 0u;
                *(uint32_t*)(kvb + (d1 >> 3) * 128 + (d1 & 7) * 2) = c == 0 ? pack_bf16(d[4], d[5]) : cst;
                *(uint32_t*)(kvb + 768 + (d1 >> 3) * 128 + (d1 & 7) * 2) = c == 0 ? pack_bf16(d[6], d[7]) : cst;
            }
            fence_async_all();
            bar_sync(1, 128);
            if (warp == 0) {
                if (lane == 0) red_release(&g_flag_kv[rb]);
                __syncwarp();
                const int tile = (rb + lane) & 31;
                bool seen = false;
                const uint32_t t0 = (uint32_t)clock();
                while (true) {
                    if (!seen && (int)(ld_acquire(&g_flag_kv[tile]) - epoch * 4u) >= 0) {
                        seen = true;
                        if (lane < 4) {
                            fence_async_all();
                            mbar_expect_tx(bars + (B_KVFULL + lane) * 8, 6144);
                            bulk_load(sb + KVR_OFF + lane * 6144, (const char*)g_kv + tile * 6144, 6144, bars + (B_KVFULL + lane) * 8);
                        }
                    }
                    if (__all_sync(~0u, seen)) break;
                    if ((uint32_t)clock() - t0 > 2000000000u) __trap();
                }
                if (lane == 0) mbar_arrive(bars + B_KVALL * 8);
            }
        }
        PROF(17);
        if (t == 0) {
            mbar_wait(bars + B_SLABFREE * 8, 0);
            for (int s = 0; s < 3; s++) issue_stage(s, sb, &tm_wq, &tm_wg, &tm_wu, &tm_wd, rb, cb, true);
        }
        __syncwarp();
        {
            float d[40];
#pragma unroll 1
            for (int s = 0; s < 5; s++) {
                const int sl = s % 3;
                mbar_wait(bars + (B_RING + sl) * 8, (s / 3) & 1);
                const uint64_t dB = mkdesc(sb + RING_OFF + sl * 32768, 4096, 512, 2);
#pragma unroll
                for (int k = 0; k < 8; k += 2) {
                    wg_fence();
                    wgmma_ss_n80(d, dXN + (2 * s + (k >> 2)) * 512 + (k & 3) * 2, dB + (k >> 2) * 768 + (k & 3) * 64, (s | k) != 0);
                    wgmma_ss_n80(d, dXN + (2 * s + (k >> 2)) * 512 + (k & 3) * 2 + 2, dB + (k >> 2) * 768 + (k & 3) * 64 + 64, 1);
                    wg_commit(); wg_wait<0>();
                }
                bar_sync(1, 128);
                if (t == 0) issue_stage(s + 3, sb, &tm_wq, &tm_wg, &tm_wu, &tm_wd, rb, cb, true);
                __syncwarp();
            }
#pragma unroll
            for (int i = 0; i < 40; i++) asm volatile("" : "+f"(d[i]) :: "memory");
            const uint32_t qa_ = sb + QO_OFF + warp * 256 + r * 16 + c * 4;
#pragma unroll
            for (int j = 0; j < 10; j++) {
                sts32(qa_ + j * 1024, pack_bf16(d[4 * j] * QSCALE, d[4 * j + 1] * QSCALE));
                sts32(qa_ + j * 1024 + 128, pack_bf16(d[4 * j + 2] * QSCALE, d[4 * j + 3] * QSCALE));
            }
            __syncwarp();
            if (lane == 0) mbar_arrive(bars + B_Q2 * 8);
        }
        PROF(18);
#pragma unroll 1
        for (int jj = 0; jj < 3; jj++) {
            float d[128];
#pragma unroll 1
            for (int kc = 0; kc < 10; kc++) {
                const int s = 5 + jj * 10 + kc, sl = s % 3;
                mbar_wait(bars + (B_RING + sl) * 8, (s / 3) & 1);
                const uint64_t dB = mkdesc(sb + RING_OFF + sl * 32768, 8192, 1024, 1);
#pragma unroll
                for (int k = 0; k < 4; k++) {
                    wg_fence();
                    wgmma_ss_n256(d, dXN + kc * 512 + k * 2, dB + k * 128, (kc | k) != 0);
                    wg_commit(); wg_wait<0>();
                }
                bar_sync(1, 128);
                if (t == 0) issue_stage(s + 3, sb, &tm_wq, &tm_wg, &tm_wu, &tm_wd, rb, cb, false);
                __syncwarp();
            }
#pragma unroll
            for (int i = 0; i < 128; i++) asm volatile("" : "+f"(d[i]) :: "memory");
            const int mrow = warp * 16 + ((lane >> 3) & 1) * 8 + (lane & 7);
            const uint32_t ha = sb + HST_OFF + mrow * 128;
#pragma unroll
            for (int j = 0; j < 16; j += 2) {
                uint32_t h[4];
#pragma unroll
                for (int i = 0; i < 4; i++)
                    h[i] = bf2_mul(pack_bf16(d[4 * j + 2 * i], d[4 * j + 2 * i + 1]), pack_bf16(d[64 + 4 * j + 2 * i], d[64 + 4 * j + 2 * i + 1]));
                const int blk = (j & 7) + (lane >> 4);
                stsm4(ha + (j >> 3) * 8192 + ((blk ^ (mrow & 7)) << 4), h[0], h[1], h[2], h[3]);
            }
            fence_async_smem();
            bar_sync(1, 128);
            if (t == 0) {
                bulk_store((char*)g_h + (size_t)(rb * 24 + cb * 6 + jj * 2) * 8192, sb + HST_OFF, 16384);
                bulk_commit_wait();
                fence_async_all();
                red_release(&g_flag_h[rb]);
            }
            __syncwarp();
            PROF(19 + jj);
        }
        uint32_t gs[40];
        {
            if (t == 0) {
                flag_wait(&g_flag_h[rb], epoch * 12u);
                fence_async_all();
                for (int s = 35; s < 38; s++)
                    bulk_load(sb + RING_OFF + (s % 3) * 32768, (const char*)g_h + (size_t)(rb * 24 + s - 35) * 8192, 8192, bars + (B_RING + s % 3) * 8);
            }
            if (warp == 1) {
                if (lane == 0) mbar_expect_tx(bars + B_XT * 8, 64 * 320);
                __syncwarp();
                for (int i = lane; i < 64; i += 32)
                    bulk_load(sb + XT_OFF + i * 336, P.x + (size_t)(rb * 64 + i) * 640 + cb * 160, 320, bars + B_XT * 8);
            }
            __syncwarp();
            PROF(22);
            float d[80];
#pragma unroll 1
            for (int kc = 0; kc < 24; kc++) {
                const int s = 35 + kc, sl = s % 3;
                mbar_wait(bars + (B_RING + sl) * 8, (s / 3) & 1);
                const uint64_t dA = mkdesc(sb + RING_OFF + sl * 32768, 16, 1024, 1);
                const uint64_t dB = mkdesc(sb + RING_OFF + sl * 32768 + 8192, 4096, 512, 2);
#pragma unroll
                for (int k = 0; k < 4; k++) {
                    wg_fence();
                    wgmma_ss_n160(d, dA + k * 2, dB + k * 64, (kc | k) != 0);
                    wg_commit(); wg_wait<0>();
                }
                bar_sync(1, 128);
                if (t == 0) issue_stage(s + 3, sb, &tm_wq, &tm_wg, &tm_wu, &tm_wd, rb, cb, true);
                __syncwarp();
            }
            if (t == 0) {
                for (int i = 0; i < 4; i++) {
                    mbar_expect_tx(bars + (B_WO + i) * 8, 25600);
                    tma3d(sb + RING_OFF + i * 25600, &tm_wo, 0, ((cb + i) & 3) * 160, cb * 5, bars + (B_WO + i) * 8);
                }
            }
            __syncwarp();
#pragma unroll
            for (int i = 0; i < 80; i++) asm volatile("" : "+f"(d[i]) :: "memory");
#pragma unroll
            for (int i = 0; i < 40; i++) {
                const uint32_t y2 = pack_bf16(d[2 * i], d[2 * i + 1]);
                const float y0 = bf_lo(y2), y1 = bf_hi(y2);
                gs[i] = pack_bf16(y0 * rcp(1.0f + ex2(y0 * -1.4426950408889634f)), y1 * rcp(1.0f + ex2(y1 * -1.4426950408889634f)));
            }
        }
        PROF(23);
        {
            float d[80];
#pragma unroll 1
            for (int pass = 0; pass < 2; pass++) {
                mbar_wait(bars + B_OREADY * 8, pass);
                PROF(24 + pass * 3);
                if (t == 0) {
                    bulk_store((char*)g_o + (size_t)(rb * 8 + pass * 4 + cb) * 10240, sb + QO_OFF, 10240);
                    bulk_commit_wait();
                    fence_async_all();
                    red_release(&g_flag_o[rb * 2 + pass]);
                }
                __syncwarp();
                {
                    mbar_wait(bars + B_WO * 8, pass);
                    const uint64_t dA = mkdesc(sb + QO_OFF, 1024, 128, 0);
                    const uint64_t dB = mkdesc(sb + RING_OFF, 5120, 512, 2);
                    wg_fence();
#pragma unroll
                    for (int k = 0; k < 5; k++) wgmma_ss_n160(d, dA + k * 128, dB + k * 64, (pass | k) != 0);
                    wg_commit();
                }
                if (t == 0) {
                    flag_wait(&g_flag_o[rb * 2 + pass], epoch * 4u);
                    fence_async_all();
                    mbar_expect_tx(bars + B_OBLOB * 8, 30720);
                    for (int i = 1; i < 4; i++)
                        bulk_load(sb + XN_OFF + (i - 1) * 10240, (const char*)g_o + (size_t)(rb * 8 + pass * 4 + ((cb + i) & 3)) * 10240, 10240, bars + B_OBLOB * 8);
                }
                __syncwarp();
                wg_wait<0>();
                PROF(25 + pass * 3);
                mbar_wait(bars + B_OBLOB * 8, pass);
#pragma unroll 1
                for (int i = 1; i < 4; i++) {
                    mbar_wait(bars + (B_WO + i) * 8, pass);
                    const uint64_t dA = mkdesc(sb + XN_OFF + (i - 1) * 10240, 1024, 128, 0);
                    const uint64_t dB = mkdesc(sb + RING_OFF + i * 25600, 5120, 512, 2);
                    wg_fence();
#pragma unroll
                    for (int k = 0; k < 5; k++) wgmma_ss_n160(d, dA + k * 128, dB + k * 64, 1);
                    wg_commit();
                    if (pass == 0) wg_wait<0>();
                }
                wg_wait<0>();
                if (pass == 0) {
                    bar_sync(1, 128);
                    if (t == 0) {
                        mbar_arrive(bars + B_QOFREE * 8);
                        for (int i = 0; i < 4; i++) {
                            mbar_expect_tx(bars + (B_WO + i) * 8, 25600);
                            tma3d(sb + RING_OFF + i * 25600, &tm_wo, 0, ((cb + i) & 3) * 160 + 80, cb * 5, bars + (B_WO + i) * 8);
                        }
                    }
                    __syncwarp();
                }
                PROF(26 + pass * 3);
            }
#pragma unroll
            for (int i = 0; i < 80; i++) asm volatile("" : "+f"(d[i]) :: "memory");
            mbar_wait(bars + B_XT * 8, 0);
            const int mrow = warp * 16 + ((lane >> 3) & 1) * 8 + (lane & 7);
            const uint32_t xa = sb + XT_OFF + mrow * 336 + (lane >> 4) * 16;
#pragma unroll
            for (int j = 0; j < 20; j += 2) {
                uint32_t x[4];
                ldsm4(xa + j * 16, x[0], x[1], x[2], x[3]);
#pragma unroll
                for (int i = 0; i < 4; i++)
                    x[i] = bf2_add(x[i], bf2_mul(pack_bf16(d[4 * j + 2 * i], d[4 * j + 2 * i + 1]), gs[2 * j + i]));
                stsm4(xa + j * 16, x[0], x[1], x[2], x[3]);
            }
            fence_async_smem();
            __syncwarp();
            if (lane < 16) {
                const int row = warp * 16 + lane;
                bulk_store(P.out + (size_t)(rb * 64 + row) * 640 + cb * 160, sb + XT_OFF + row * 336, 320);
                bulk_commit_wait();
            }
            if (t == 0) g_epoch[bid] = epoch;
            PROF(30);
        }
    }
}

typedef CUresult (*EncodeFn)(CUtensorMap*, CUtensorMapDataType, cuuint32_t, void*, const cuuint64_t*, const cuuint64_t*, const cuuint32_t*,
                             const cuuint32_t*, CUtensorMapInterleave, CUtensorMapSwizzle, CUtensorMapL2promotion, CUtensorMapFloatOOBfill);

static void make_map(EncodeFn enc, CUtensorMap* m, const void* base, int K, int N, int grp, int boxk, int ngrp, CUtensorMapSwizzle sw) {
    cuuint32_t es[3] = {1, 1, 1};
    if (ngrp == 0) {
        cuuint64_t dims[2] = {(cuuint64_t)N, (cuuint64_t)K};
        cuuint64_t str[1] = {(cuuint64_t)N * 2};
        cuuint32_t box[2] = {(cuuint32_t)grp, (cuuint32_t)boxk};
        enc(m, CU_TENSOR_MAP_DATA_TYPE_BFLOAT16, 2, (void*)base, dims, str, box, es, CU_TENSOR_MAP_INTERLEAVE_NONE, sw,
            CU_TENSOR_MAP_L2_PROMOTION_L2_128B, CU_TENSOR_MAP_FLOAT_OOB_FILL_NONE);
    } else {
        cuuint64_t dims[3] = {(cuuint64_t)grp, (cuuint64_t)K, (cuuint64_t)(N / grp)};
        cuuint64_t str[2] = {(cuuint64_t)N * 2, (cuuint64_t)grp * 2};
        cuuint32_t box[3] = {(cuuint32_t)grp, (cuuint32_t)boxk, (cuuint32_t)ngrp};
        enc(m, CU_TENSOR_MAP_DATA_TYPE_BFLOAT16, 3, (void*)base, dims, str, box, es, CU_TENSOR_MAP_INTERLEAVE_NONE, sw,
            CU_TENSOR_MAP_L2_PROMOTION_L2_128B, CU_TENSOR_MAP_FLOAT_OOB_FILL_NONE);
    }
}

}

extern "C" void kernel_launch(void* const* d_in, const int* in_sizes, int n_in, void* d_out, int out_size) {
    using namespace mk;
    void* fn = nullptr;
    cudaDriverEntryPointQueryResult qr;
    cudaGetDriverEntryPoint("cuTensorMapEncodeTiled", &fn, cudaEnableDefault, &qr);
    EncodeFn enc = (EncodeFn)fn;
    Params P;
    P.x = (const __nv_bfloat16*)d_in[0]; P.wq = (const __nv_bfloat16*)d_in[1]; P.wk = (const __nv_bfloat16*)d_in[2];
    P.wv = (const __nv_bfloat16*)d_in[3]; P.wo = (const __nv_bfloat16*)d_in[4]; P.wg = (const __nv_bfloat16*)d_in[6];
    P.wu = (const __nv_bfloat16*)d_in[7]; P.wd = (const __nv_bfloat16*)d_in[8]; P.out = (__nv_bfloat16*)d_out;
    CUtensorMap tq, tg, tu, td, to;
    make_map(enc, &tq, P.wq, 640, 640, 32, 64, 0, CU_TENSOR_MAP_SWIZZLE_64B);
    make_map(enc, &tg, P.wg, 640, 1536, 64, 64, 2, CU_TENSOR_MAP_SWIZZLE_128B);
    make_map(enc, &tu, P.wu, 640, 1536, 64, 64, 2, CU_TENSOR_MAP_SWIZZLE_128B);
    make_map(enc, &td, P.wd, 1536, 640, 32, 64, 5, CU_TENSOR_MAP_SWIZZLE_64B);
    make_map(enc, &to, P.wo, 640, 640, 32, 80, 5, CU_TENSOR_MAP_SWIZZLE_64B);
    cudaFuncSetAttribute(fused_kernel, cudaFuncAttributeMaxDynamicSharedMemorySize, SMEM_TOTAL);
    fused_kernel<<<128, 384, SMEM_TOTAL, cudaStreamPerThread>>>(tq, tg, tu, td, to, P);
}
```

```cpp
#include <cuda_runtime.h>
#include <cuda_bf16.h>
#include <cuda.h>
#include <stdint.h>

#define PMASK 0x11011101u
#define PDEG 4

namespace mk {

constexpr uint32_t XN_OFF = 0, RING_OFF = 81920, HST_OFF = 180224, QO_OFF = 196608, KVR_OFF = 206848, BAR_OFF = 231424,
                   SMEM_TOTAL = 232448;
constexpr uint32_t XT_OFF = XN_OFF + 40960;
enum { B_SLAB = 0, B_SLABFREE = 1, B_KVFULL = 2, B_KVALL = 6, B_RING = 7, B_Q2 = 10, B_OREADY = 11, B_QOFREE = 12,
       B_WO = 13, B_OBLOB = 17, B_XT = 18, B_KVEMPTY = 19, B_REMPTY = 23, B_HFULL = 26, B_HFREE = 27, B_WODONE = 28, NBAR = 29 };

__device__ uint4 g_kv[32 * 6144 / 16];
__device__ uint4 g_h[32 * 24 * 8192 / 16];
__device__ uint4 g_o[32 * 8 * 10240 / 16];
__device__ unsigned g_flag_kv[32];
__device__ unsigned g_flag_h[32];
__device__ unsigned g_flag_o[64];
__device__ unsigned g_epoch[128];
#define PROF(i)
#define PROFV(i, v)
#define PW_BEGIN()
#define PW_END(acc)

__device__ __forceinline__ void wgmma_rs_n24_t1(float (&d)[12], uint32_t a0, uint32_t a1, uint32_t a2, uint32_t a3, uint64_t desc, int scale_d) {
    asm volatile("{\n.reg .pred p;\nsetp.ne.b32 p, %17, 0;\n"
        "wgmma.mma_async.sync.aligned.m64n24k16.f32.bf16.bf16 {%0, %1, %2, %3, %4, %5, %6, %7, %8, %9, %10, %11}, {%12, %13, %14, %15}, %16, p, 1, 1, 1;\n}\n"
        : "+f"(d[0]), "+f"(d[1]), "+f"(d[2]), "+f"(d[3]), "+f"(d[4]), "+f"(d[5]), "+f"(d[6]), "+f"(d[7]), "+f"(d[8]), "+f"(d[9]), "+f"(d[10]), "+f"(d[11])
        : "r"(a0), "r"(a1), "r"(a2), "r"(a3), "l"(desc), "r"(scale_d));
}
__device__ __forceinline__ void wgmma_rs_n64_t0(float (&d)[32], uint32_t a0, uint32_t a1, uint32_t a2, uint32_t a3, uint64_t desc, int scale_d) {
    asm volatile("{\n.reg .pred p;\nsetp.ne.b32 p, %37, 0;\n"
        "wgmma.mma_async.sync.aligned.m64n64k16.f32.bf16.bf16 {%0, %1, %2, %3, %4, %5, %6, %7, %8, %9, %10, %11, %12, %13, %14, %15, %16, %17, %18, %19, %20, %21, %22, %23, %24, %25, %26, %27, %28, %29, %30, %31}, {%32, %33, %34, %35}, %36, p, 1, 1, 0;\n}\n"
        : "+f"(d[0]), "+f"(d[1]), "+f"(d[2]), "+f"(d[3]), "+f"(d[4]), "+f"(d[5]), "+f"(d[6]), "+f"(d[7]), "+f"(d[8]), "+f"(d[9]), "+f"(d[10]), "+f"(d[11]), "+f"(d[12]), "+f"(d[13]), "+f"(d[14]), "+f"(d[15]), "+f"(d[16]), "+f"(d[17]), "+f"(d[18]), "+f"(d[19]), "+f"(d[20]), "+f"(d[21]), "+f"(d[22]), "+f"(d[23]), "+f"(d[24]), "+f"(d[25]), "+f"(d[26]), "+f"(d[27]), "+f"(d[28]), "+f"(d[29]), "+f"(d[30]), "+f"(d[31])
        : "r"(a0), "r"(a1), "r"(a2), "r"(a3), "l"(desc), "r"(scale_d));
}
__device__ __forceinline__ void wgmma_ss_n16(float (&d)[8], uint64_t da, uint64_t db, int scale_d) {
    asm volatile("{\n.reg .pred p;\nsetp.ne.b32 p, %10, 0;\n"
        "wgmma.mma_async.sync.aligned.m64n16k16.f32.bf16.bf16 {%0, %1, %2, %3, %4, %5, %6, %7}, %8, %9, p, 1, 1, 0, 1;\n}\n"
        : "+f"(d[0]), "+f"(d[1]), "+f"(d[2]), "+f"(d[3]), "+f"(d[4]), "+f"(d[5]), "+f"(d[6]), "+f"(d[7])
        : "l"(da), "l"(db), "r"(scale_d));
}
__device__ __forceinline__ void wgmma_ss_n48(float (&d)[24], uint64_t da, uint64_t db, int scale_d) {
    asm volatile("{\n.reg .pred p;\nsetp.ne.b32 p, %26, 0;\n"
        "wgmma.mma_async.sync.aligned.m64n48k16.f32.bf16.bf16 {%0, %1, %2, %3, %4, %5, %6, %7, %8, %9, %10, %11, %12, %13, %14, %15, %16, %17, %18, %19, %20, %21, %22, %23}, %24, %25, p, 1, 1, 0, 1;\n}\n"
        : "+f"(d[0]), "+f"(d[1]), "+f"(d[2]), "+f"(d[3]), "+f"(d[4]), "+f"(d[5]), "+f"(d[6]), "+f"(d[7]), "+f"(d[8]), "+f"(d[9]), "+f"(d[10]), "+f"(d[11]), "+f"(d[12]), "+f"(d[13]), "+f"(d[14]), "+f"(d[15]), "+f"(d[16]), "+f"(d[17]), "+f"(d[18]), "+f"(d[19]), "+f"(d[20]), "+f"(d[21]), "+f"(d[22]), "+f"(d[23])
        : "l"(da), "l"(db), "r"(scale_d));
}
__device__ __forceinline__ void wgmma_ss_n80(float (&d)[40], uint64_t da, uint64_t db, int scale_d) {
    asm volatile("{\n.reg .pred p;\nsetp.ne.b32 p, %42, 0;\n"
        "wgmma.mma_async.sync.aligned.m64n80k16.f32.bf16.bf16 {%0, %1, %2, %3, %4, %5, %6, %7, %8, %9, %10, %11, %12, %13, %14, %15, %16, %17, %18, %19, %20, %21, %22, %23, %24, %25, %26, %27, %28, %29, %30, %31, %32, %33, %34, %35, %36, %37, %38, %39}, %40, %41, p, 1, 1, 0, 1;\n}\n"
        : "+f"(d[0]), "+f"(d[1]), "+f"(d[2]), "+f"(d[3]), "+f"(d[4]), "+f"(d[5]), "+f"(d[6]), "+f"(d[7]), "+f"(d[8]), "+f"(d[9]), "+f"(d[10]), "+f"(d[11]), "+f"(d[12]), "+f"(d[13]), "+f"(d[14]), "+f"(d[15]), "+f"(d[16]), "+f"(d[17]), "+f"(d[18]), "+f"(d[19]), "+f"(d[20]), "+f"(d[21]), "+f"(d[22]), "+f"(d[23]), "+f"(d[24]), "+f"(d[25]), "+f"(d[26]), "+f"(d[27]), "+f"(d[28]), "+f"(d[29]), "+f"(d[30]), "+f"(d[31]), "+f"(d[32]), "+f"(d[33]), "+f"(d[34]), "+f"(d[35]), "+f"(d[36]), "+f"(d[37]), "+f"(d[38]), "+f"(d[39])
        : "l"(da), "l"(db), "r"(scale_d));
}
__device__ __forceinline__ void wgmma_ss_n128(float (&d)[64], uint64_t da, uint64_t db, int scale_d) {
    asm volatile("{\n.reg .pred p;\nsetp.ne.b32 p, %66, 0;\n"
        "wgmma.mma_async.sync.aligned.m64n128k16.f32.bf16.bf16 {%0, %1, %2, %3, %4, %5, %6, %7, %8, %9, %10, %11, %12, %13, %14, %15, %16, %17, %18, %19, %20, %21, %22, %23, %24, %25, %26, %27, %28, %29, %30, %31, %32, %33, %34, %35, %36, %37, %38, %39, %40, %41, %42, %43, %44, %45, %46, %47, %48, %49, %50, %51, %52, %53, %54, %55, %56, %57, %58, %59, %60, %61, %62, %63}, %64, %65, p, 1, 1, 0, 1;\n}\n"
        : "+f"(d[0]), "+f"(d[1]), "+f"(d[2]), "+f"(d[3]), "+f"(d[4]), "+f"(d[5]), "+f"(d[6]), "+f"(d[7]), "+f"(d[8]), "+f"(d[9]), "+f"(d[10]), "+f"(d[11]), "+f"(d[12]), "+f"(d[13]), "+f"(d[14]), "+f"(d[15]), "+f"(d[16]), "+f"(d[17]), "+f"(d[18]), "+f"(d[19]), "+f"(d[20]), "+f"(d[21]), "+f"(d[22]), "+f"(d[23]), "+f"(d[24]), "+f"(d[25]), "+f"(d[26]), "+f"(d[27]), "+f"(d[28]), "+f"(d[29]), "+f"(d[30]), "+f"(d[31]), "+f"(d[32]), "+f"(d[33]), "+f"(d[34]), "+f"(d[35]), "+f"(d[36]), "+f"(d[37]), "+f"(d[38]), "+f"(d[39]), "+f"(d[40]), "+f"(d[41]), "+f"(d[42]), "+f"(d[43]), "+f"(d[44]), "+f"(d[45]), "+f"(d[46]), "+f"(d[47]), "+f"(d[48]), "+f"(d[49]), "+f"(d[50]), "+f"(d[51]), "+f"(d[52]), "+f"(d[53]), "+f"(d[54]), "+f"(d[55]), "+f"(d[56]), "+f"(d[57]), "+f"(d[58]), "+f"(d[59]), "+f"(d[60]), "+f"(d[61]), "+f"(d[62]), "+f"(d[63])
        : "l"(da), "l"(db), "r"(scale_d));
}
__device__ __forceinline__ void wgmma_ss_n160(float (&d)[80], uint64_t da, uint64_t db, int scale_d) {
    asm volatile("{\n.reg .pred p;\nsetp.ne.b32 p, %82, 0;\n"
        "wgmma.mma_async.sync.aligned.m64n160k16.f32.bf16.bf16 {%0, %1, %2, %3, %4, %5, %6, %7, %8, %9, %10, %11, %12, %13, %14, %15, %16, %17, %18, %19, %20, %21, %22, %23, %24, %25, %26, %27, %28, %29, %30, %31, %32, %33, %34, %35, %36, %37, %38, %39, %40, %41, %42, %43, %44, %45, %46, %47, %48, %49, %50, %51, %52, %53, %54, %55, %56, %57, %58, %59, %60, %61, %62, %63, %64, %65, %66, %67, %68, %69, %70, %71, %72, %73, %74, %75, %76, %77, %78, %79}, %80, %81, p, 1, 1, 0, 1;\n}\n"
        : "+f"(d[0]), "+f"(d[1]), "+f"(d[2]), "+f"(d[3]), "+f"(d[4]), "+f"(d[5]), "+f"(d[6]), "+f"(d[7]), "+f"(d[8]), "+f"(d[9]), "+f"(d[10]), "+f"(d[11]), "+f"(d[12]), "+f"(d[13]), "+f"(d[14]), "+f"(d[15]), "+f"(d[16]), "+f"(d[17]), "+f"(d[18]), "+f"(d[19]), "+f"(d[20]), "+f"(d[21]), "+f"(d[22]), "+f"(d[23]), "+f"(d[24]), "+f"(d[25]), "+f"(d[26]), "+f"(d[27]), "+f"(d[28]), "+f"(d[29]), "+f"(d[30]), "+f"(d[31]), "+f"(d[32]), "+f"(d[33]), "+f"(d[34]), "+f"(d[35]), "+f"(d[36]), "+f"(d[37]), "+f"(d[38]), "+f"(d[39]), "+f"(d[40]), "+f"(d[41]), "+f"(d[42]), "+f"(d[43]), "+f"(d[44]), "+f"(d[45]), "+f"(d[46]), "+f"(d[47]), "+f"(d[48]), "+f"(d[49]), "+f"(d[50]), "+f"(d[51]), "+f"(d[52]), "+f"(d[53]), "+f"(d[54]), "+f"(d[55]), "+f"(d[56]), "+f"(d[57]), "+f"(d[58]), "+f"(d[59]), "+f"(d[60]), "+f"(d[61]), "+f"(d[62]), "+f"(d[63]), "+f"(d[64]), "+f"(d[65]), "+f"(d[66]), "+f"(d[67]), "+f"(d[68]), "+f"(d[69]), "+f"(d[70]), "+f"(d[71]), "+f"(d[72]), "+f"(d[73]), "+f"(d[74]), "+f"(d[75]), "+f"(d[76]), "+f"(d[77]), "+f"(d[78]), "+f"(d[79])
        : "l"(da), "l"(db), "r"(scale_d));
}

__device__ __forceinline__ uint32_t smem_u32(const void* p) { return (uint32_t)__cvta_generic_to_shared(p); }
__device__ __forceinline__ void wg_fence() { asm volatile("wgmma.fence.sync.aligned;" ::: "memory"); }
__device__ __forceinline__ void wg_commit() { asm volatile("wgmma.commit_group.sync.aligned;" ::: "memory"); }
template <int N> __device__ __forceinline__ void wg_wait() { asm volatile("wgmma.wait_group.sync.aligned %0;" :: "n"(N) : "memory"); }
__device__ __forceinline__ uint64_t mkdesc(uint32_t addr, uint32_t lbo, uint32_t sbo, uint32_t mode) {
    return (uint64_t)((addr & 0x3FFFF) >> 4) | ((uint64_t)(lbo >> 4) << 16) | ((uint64_t)(sbo >> 4) << 32) | ((uint64_t)mode << 62);
}
__device__ __forceinline__ void mbar_init(uint32_t bar, int cnt) { asm volatile("mbarrier.init.shared::cta.b64 [%0], %1;" :: "r"(bar), "r"(cnt) : "memory"); }
__device__ __forceinline__ void mbar_expect_tx(uint32_t bar, uint32_t bytes) { asm volatile("mbarrier.arrive.expect_tx.shared::cta.b64 _, [%0], %1;" :: "r"(bar), "r"(bytes) : "memory"); }
__device__ __forceinline__ void mbar_arrive(uint32_t bar) { asm volatile("mbarrier.arrive.shared::cta.b64 _, [%0];" :: "r"(bar) : "memory"); }
__device__ __forceinline__ bool mbar_try(uint32_t bar, uint32_t parity) {
    uint32_t ok;
    asm volatile("{\n.reg .pred p;\nmbarrier.try_wait.parity.shared::cta.b64 p, [%1], %2;\nselp.b32 %0, 1, 0, p;\n}" : "=r"(ok) : "r"(bar), "r"(parity) : "memory");
    return ok != 0;
}
__device__ __forceinline__ void mbar_wait(uint32_t bar, uint32_t parity) {
    asm volatile("{\n.reg .pred p;\n.reg .u32 n;\nmov.u32 n, 0;\n"
                 "WL:\nmbarrier.try_wait.parity.shared::cta.b64 p, [%0], %1;\n@p bra WD;\n"
                 "add.u32 n, n, 1;\nsetp.lt.u32 p, n, 2000000;\n@p bra WL;\ntrap;\nWD:\n}" :: "r"(bar), "r"(parity) : "memory");
}
__device__ __forceinline__ void mbar_arrive_if(uint32_t bar, bool pred) {
    asm volatile("{\n.reg .pred p;\nsetp.ne.u32 p, %1, 0;\n@p mbarrier.arrive.shared::cta.b64 _, [%0];\n}" :: "r"(bar), "r"((uint32_t)pred) : "memory");
}
__device__ __forceinline__ uint32_t ld_acquire(const unsigned* p) { uint32_t v; asm volatile("ld.acquire.gpu.global.u32 %0, [%1];" : "=r"(v) : "l"(p) : "memory"); return v; }
__device__ __forceinline__ void red_release(unsigned* p) { asm volatile("red.release.gpu.global.add.u32 [%0], 1;" :: "l"(p) : "memory"); }
__device__ __forceinline__ void flag_wait(const unsigned* p, uint32_t target) {
    uint32_t it = 0;
    while ((int)(ld_acquire(p) - target) < 0) { if (++it > 4000000u) __trap(); }
}
__device__ __forceinline__ void fence_async_glob() { asm volatile("fence.proxy.async.global;" ::: "memory"); }
__device__ __forceinline__ void fence_async_smem() { asm volatile("fence.proxy.async.shared::cta;" ::: "memory"); }
__device__ __forceinline__ void bar_sync(int id, int n) { asm volatile("bar.sync %0, %1;" :: "r"(id), "r"(n) : "memory"); }
__device__ __forceinline__ void bulk_load(uint32_t dst, const void* src, uint32_t bytes, uint32_t bar) {
    asm volatile("cp.async.bulk.shared::cluster.global.mbarrier::complete_tx::bytes [%0], [%1], %2, [%3];" :: "r"(dst), "l"(src), "r"(bytes), "r"(bar) : "memory");
}
__device__ __forceinline__ void bulk_store(void* dst, uint32_t src, uint32_t bytes) {
    asm volatile("cp.async.bulk.global.shared::cta.bulk_group [%0], [%1], %2;" :: "l"(dst), "r"(src), "r"(bytes) : "memory");
}
__device__ __forceinline__ void bulk_commit_wait() {
    asm volatile("cp.async.bulk.commit_group;" ::: "memory");
    asm volatile("cp.async.bulk.wait_group 0;" ::: "memory");
}
__device__ __forceinline__ void l2_prefetch(const void* src, uint32_t bytes) { asm volatile("cp.async.bulk.prefetch.L2.global [%0], %1;" :: "l"(src), "r"(bytes) : "memory"); }
__device__ __forceinline__ void tma2d(uint32_t dst, const CUtensorMap* tm, int c0, int c1, uint32_t bar) {
    asm volatile("cp.async.bulk.tensor.2d.shared::cluster.global.mbarrier::complete_tx::bytes [%0], [%1, {%3, %4}], [%2];"
                 :: "r"(dst), "l"(tm), "r"(bar), "r"(c0), "r"(c1) : "memory");
}
__device__ __forceinline__ void tma3d(uint32_t dst, const CUtensorMap* tm, int c0, int c1, int c2, uint32_t bar) {
    asm volatile("cp.async.bulk.tensor.3d.shared::cluster.global.mbarrier::complete_tx::bytes [%0], [%1, {%3, %4, %5}], [%2];"
                 :: "r"(dst), "l"(tm), "r"(bar), "r"(c0), "r"(c1), "r"(c2) : "memory");
}
__device__ __forceinline__ void sts32(uint32_t a, uint32_t v) { asm volatile("st.shared.b32 [%0], %1;" :: "r"(a), "r"(v) : "memory"); }
__device__ __forceinline__ uint32_t lds32(uint32_t a) { uint32_t v; asm volatile("ld.shared.b32 %0, [%1];" : "=r"(v) : "r"(a) : "memory"); return v; }
__device__ __forceinline__ void sts128(uint32_t a, uint32_t x, uint32_t y, uint32_t z, uint32_t w) { asm volatile("st.shared.v4.b32 [%0], {%1, %2, %3, %4};" :: "r"(a), "r"(x), "r"(y), "r"(z), "r"(w) : "memory"); }
__device__ __forceinline__ void stsm4(uint32_t a, uint32_t x, uint32_t y, uint32_t z, uint32_t w) { asm volatile("stmatrix.sync.aligned.m8n8.x4.shared.b16 [%0], {%1, %2, %3, %4};" :: "r"(a), "r"(x), "r"(y), "r"(z), "r"(w) : "memory"); }
__device__ __forceinline__ void ldsm4(uint32_t a, uint32_t& x, uint32_t& y, uint32_t& z, uint32_t& w) { asm volatile("ldmatrix.sync.aligned.m8n8.x4.shared.b16 {%0, %1, %2, %3}, [%4];" : "=r"(x), "=r"(y), "=r"(z), "=r"(w) : "r"(a) : "memory"); }
__device__ __forceinline__ float ex2(float x) { float y; asm("ex2.approx.ftz.f32 %0, %1;" : "=f"(y) : "f"(x)); return y; }
__device__ __forceinline__ float rcp(float x) { float y; asm("rcp.approx.ftz.f32 %0, %1;" : "=f"(y) : "f"(x)); return y; }
__device__ __forceinline__ uint32_t pack_bf16(float lo, float hi) { uint32_t r; asm("cvt.rn.bf16x2.f32 %0, %1, %2;" : "=r"(r) : "f"(hi), "f"(lo)); return r; }
__device__ __forceinline__ float bf_lo(uint32_t v) { return __uint_as_float(v << 16); }
__device__ __forceinline__ float bf_hi(uint32_t v) { return __uint_as_float(v & 0xffff0000u); }
__device__ __forceinline__ float bf_round(float x) { return bf_lo(pack_bf16(x, 0.f)); }
__device__ __forceinline__ uint32_t bf2_sub(uint32_t a, uint32_t b) { uint32_t r; asm("sub.rn.bf16x2 %0, %1, %2;" : "=r"(r) : "r"(a), "r"(b)); return r; }
__device__ __forceinline__ uint32_t bf2_add(uint32_t a, uint32_t b) { uint32_t r; asm("add.rn.bf16x2 %0, %1, %2;" : "=r"(r) : "r"(a), "r"(b)); return r; }
__device__ __forceinline__ uint32_t bf2_mul(uint32_t a, uint32_t b) { uint32_t r; asm("mul.rn.bf16x2 %0, %1, %2;" : "=r"(r) : "r"(a), "r"(b)); return r; }

__device__ __forceinline__ float ex2_poly(float x) {
    float u;
    asm("fma.rn.sat.f32 %0, %1, %2, %3;" : "=f"(u) : "f"(x), "f"(1.0f / 254.0f), "f"(126.0f / 254.0f));
    const float MG = 12582912.0f - 126.0f;
    float t = fmaf(u, 254.0f, MG);
    float n2 = MG - t;
    float f = fmaf(u, 254.0f, n2);
    float p;
    p = fmaf(0.009570102207362652f, f, 0.05591785907745361f);
    p = fmaf(p, f, 0.240247443318367f);
    p = fmaf(p, f, 0.6931217908859253f);
    p = fmaf(p, f, 0.9999992847442627f);
    return __uint_as_float(__float_as_uint(p) + (__float_as_uint(t) << 23));
}
template <int C>
__device__ __forceinline__ void chunk(const float (&s)[32], uint32_t (&p)[16]) {
#pragma unroll
    for (int i = 4 * C; i < 4 * C + 4; i++) {
        float a = ((PMASK >> (2 * i)) & 1) ? ex2_poly(s[2 * i]) : ex2(s[2 * i]);
        float b = ((PMASK >> (2 * i + 1)) & 1) ? ex2_poly(s[2 * i + 1]) : ex2(s[2 * i + 1]);
        p[i] = pack_bf16(a, b);
    }
}
#define PV(o, p, C, d) wgmma_rs_n24_t1(o, p[4 * C], p[4 * C + 1], p[4 * C + 2], p[4 * C + 3], (d) + 96 * C, 1)
#define QK0(s, q, d) wgmma_rs_n64_t0(s, q[0], q[1], q[2], q[3], d, 0)
#define QK1(s, q, d) wgmma_rs_n64_t0(s, q[4], q[5], 0u, 0u, (d) + 16, 1)

__device__ __noinline__ void attn_exact_row(uint32_t qo, int row, int col0) {
    float q[20], o[20];
#pragma unroll
    for (int d = 0; d < 20; d += 2) {
        const int col = col0 + d;
        uint32_t v = lds32(qo + (col >> 3) * 1024 + (row >> 3) * 128 + (row & 7) * 16 + (col & 7) * 2);
        q[d] = bf_lo(v); q[d + 1] = bf_hi(v); o[d] = 0.f; o[d + 1] = 0.f;
    }
    float m = -INFINITY, l = 0.f;
    const uint32_t* kv = (const uint32_t*)g_kv;
#pragma unroll 1
    for (int key = 0; key < 2048; key++) {
        const uint32_t* p = kv + (key >> 3) * 192 + (key & 7) * 4;
        float s = 0.f;
#pragma unroll
        for (int d = 0; d < 20; d += 2) {
            uint32_t v = __ldcg(p + (d >> 3) * 32 + ((d & 7) >> 1));
            s = fmaf(q[d], bf_lo(v), s); s = fmaf(q[d + 1], bf_hi(v), s);
        }
        const float mn = fmaxf(m, s);
        const float sc = exp2f(m - mn), e = exp2f(s - mn);
        m = mn; l = l * sc + e;
#pragma unroll
        for (int d = 0; d < 20; d += 2) {
            uint32_t v = __ldcg(p + 96 + (d >> 3) * 32 + ((d & 7) >> 1));
            o[d] = fmaf(e, bf_lo(v), o[d] * sc); o[d + 1] = fmaf(e, bf_hi(v), o[d + 1] * sc);
        }
    }
    const float il = 1.0f / l;
#pragma unroll
    for (int d = 0; d < 20; d += 2) {
        const int col = col0 + d;
        sts32(qo + (col >> 3) * 1024 + (row >> 3) * 128 + (row & 7) * 16 + (col & 7) * 2, pack_bf16(o[d] * il, o[d + 1] * il));
    }
}

struct Params {
    const __nv_bfloat16 *x, *wq, *wk, *wv, *wo, *wg, *wu, *wd;
    __nv_bfloat16* out;
};

__global__ void __launch_bounds__(512, 1)
fused_kernel(const __grid_constant__ CUtensorMap tm_wq, const __grid_constant__ CUtensorMap tm_wg, const __grid_constant__ CUtensorMap tm_wu,
             const __grid_constant__ CUtensorMap tm_wd, const __grid_constant__ CUtensorMap tm_wo, const Params P) {
    extern __shared__ __align__(1024) char smem_raw[];
    const uint32_t sb = smem_u32(smem_raw);
    const uint32_t bars = sb + BAR_OFF;
    const int tid = threadIdx.x, lane = tid & 31;
    const int warp_id = __shfl_sync(~0u, tid >> 5, 0);
    const int wg = warp_id >> 2, warp = warp_id & 3;
    const int r = lane >> 2, c = lane & 3;
    const int bid = blockIdx.x;
    const int rb = ((bid >> 3) << 1) | (bid & 1), cb = (bid >> 1) & 3;
    constexpr float QSCALE = 0.22360679774997896f * 1.4426950408889634f;

    uint32_t epoch = 0;
    {
        const int row = warp_id * 4 + (lane >> 3), j = lane & 7;
        const uint4* xr = (const uint4*)(P.x + (size_t)(rb * 64 + row) * 640) + j;
        uint4 v[10];
#pragma unroll
        for (int t = 0; t < 10; t++) v[t] = __ldg(xr + 8 * t);
        const uint32_t* wsrc = (const uint32_t*)((cb < 2 ? P.wk : P.wv) + (cb & 1) * 10);
        uint32_t w0[5], w1[5];
#pragma unroll
        for (int i = 0; i < 5; i++) { w0[i] = __ldg(wsrc + tid * 10 + i); w1[i] = wg == 3 ? __ldg(wsrc + (tid + 128) * 10 + i) : 0u; }
        if (wg == 3) epoch = *(volatile unsigned*)&g_epoch[bid] + 1u;
        if (warp_id == 13) {
            if (lane == 0) {
                mbar_init(bars + B_SLAB * 8, 1); mbar_init(bars + B_SLABFREE * 8, 8);
                for (int i = 0; i < 4; i++) { mbar_init(bars + (B_KVFULL + i) * 8, 1); mbar_init(bars + (B_KVEMPTY + i) * 8, 8); mbar_init(bars + (B_WO + i) * 8, 1); }
                for (int i = 0; i < 3; i++) { mbar_init(bars + (B_RING + i) * 8, 1); mbar_init(bars + (B_REMPTY + i) * 8, 4); }
                mbar_init(bars + B_KVALL * 8, 1);
                mbar_init(bars + B_Q2 * 8, 4); mbar_init(bars + B_OREADY * 8, 8); mbar_init(bars + B_QOFREE * 8, 1);
                mbar_init(bars + B_OBLOB * 8, 1); mbar_init(bars + B_XT * 8, 1);
                mbar_init(bars + B_HFULL * 8, 4); mbar_init(bars + B_HFREE * 8, 1); mbar_init(bars + B_WODONE * 8, 4);
                asm volatile("fence.mbarrier_init.release.cluster;" ::: "memory");
                fence_async_smem();
                mbar_expect_tx(bars + B_SLAB * 8, 122880);
            }
            __syncwarp();
        }
        float s0 = 0.f, s1 = 0.f, s2 = 0.f, s3 = 0.f;
#pragma unroll
        for (int t = 0; t < 10; t++) {
            s0 += bf_lo(v[t].x); s1 += bf_hi(v[t].x); s2 += bf_lo(v[t].y); s3 += bf_hi(v[t].y);
            s0 += bf_lo(v[t].z); s1 += bf_hi(v[t].z); s2 += bf_lo(v[t].w); s3 += bf_hi(v[t].w);
        }
        float s = (s0 + s1) + (s2 + s3);
        if (wg < 3) PROF(24 + wg);
        asm volatile("" :: "f"(s) : "memory");
        if (warp_id == 13) {
            if (lane < 30) tma2d(sb + RING_OFF + lane * 4096, &tm_wq, cb * 160 + 32 * (lane % 3), (lane / 3) * 64, bars + B_SLAB * 8);
            __syncwarp();
        }
        s += __shfl_xor_sync(~0u, s, 1); s += __shfl_xor_sync(~0u, s, 2); s += __shfl_xor_sync(~0u, s, 4);
        const float mean = s * (1.0f / 640.0f);
        s0 = s1 = s2 = s3 = 0.f;
#pragma unroll
        for (int t = 0; t < 10; t++) {
            float a;
            a = bf_lo(v[t].x) - mean; s0 = fmaf(a, a, s0); a = bf_hi(v[t].x) - mean; s1 = fmaf(a, a, s1);
            a = bf_lo(v[t].y) - mean; s2 = fmaf(a, a, s2); a = bf_hi(v[t].y) - mean; s3 = fmaf(a, a, s3);
            a = bf_lo(v[t].z) - mean; s0 = fmaf(a, a, s0); a = bf_hi(v[t].z) - mean; s1 = fmaf(a, a, s1);
            a = bf_lo(v[t].w) - mean; s2 = fmaf(a, a, s2); a = bf_hi(v[t].w) - mean; s3 = fmaf(a, a, s3);
        }
        s = (s0 + s1) + (s2 + s3);
        s += __shfl_xor_sync(~0u, s, 1); s += __shfl_xor_sync(~0u, s, 2); s += __shfl_xor_sync(~0u, s, 4);
        const float var = bf_round(s * (1.0f / 640.0f));
        const float rinv = 1.0f / bf_round(sqrtf(bf_round(var + 1e-5f)));
        const uint32_t m2 = pack_bf16(mean, mean);
        const uint32_t xa = sb + XN_OFF + row * 128 + ((j ^ (row & 7)) << 4);
#pragma unroll
        for (int t = 0; t < 10; t++) {
            uint32_t d0 = bf2_sub(v[t].x, m2), d1 = bf2_sub(v[t].y, m2), d2 = bf2_sub(v[t].z, m2), d3 = bf2_sub(v[t].w, m2);
            sts128(xa + t * 8192,
                   pack_bf16(bf_lo(d0) * rinv, bf_hi(d0) * rinv), pack_bf16(bf_lo(d1) * rinv, bf_hi(d1) * rinv),
                   pack_bf16(bf_lo(d2) * rinv, bf_hi(d2) * rinv), pack_bf16(bf_lo(d3) * rinv, bf_hi(d3) * rinv));
        }
        {
            const uint32_t a = sb + KVR_OFF + (tid >> 3) * 256 + (tid & 7) * 16;
            sts128(a, w0[0], w0[1], w0[2], w0[3]);
            sts128(a + 128, w0[4], 0u, 0u, 0u);
            if (wg == 3) {
                sts128(a + 4096, w1[0], w1[1], w1[2], w1[3]);
                sts128(a + 4096 + 128, w1[4], 0u, 0u, 0u);
            }
        }
        fence_async_smem();
        if (wg < 2) PROF(0 + wg * 8);
        __syncthreads();
        if (wg == 3) PROF(27);
    }

    if (wg < 2) {
        asm volatile("setmaxnreg.inc.sync.aligned.u32 152;");
        uint32_t qa[6], qb[6];
        {
            float d[24];
            mbar_wait(bars + B_SLAB * 8, 0);
            bar_sync(2, 384);
            const uint64_t dA = mkdesc(sb + XN_OFF, 16, 1024, 1);
            const uint64_t dB = mkdesc(sb + RING_OFF + wg * 4096, 4096, 512, 2);
            wg_fence();
#pragma unroll
            for (int kc = 0; kc < 10; kc++) {
#pragma unroll
                for (int k = 0; k < 4; k++) wgmma_ss_n48(d, dA + kc * 512 + k * 2, dB + kc * 768 + k * 64, (kc | k) != 0);
            }
            wg_commit();
            wg_wait<0>();
#pragma unroll
            for (int i = 0; i < 24; i++) asm volatile("" : "+f"(d[i]) :: "memory");
            if (lane == 0) mbar_arrive(bars + B_SLABFREE * 8);
            uint32_t p0[5], p1[5];
#pragma unroll
            for (int i = 0; i < 5; i++) {
                p0[i] = pack_bf16((wg ? d[4 * i + 4] : d[4 * i]) * QSCALE, (wg ? d[4 * i + 5] : d[4 * i + 1]) * QSCALE);
                p1[i] = pack_bf16((wg ? d[4 * i + 6] : d[4 * i + 2]) * QSCALE, (wg ? d[4 * i + 7] : d[4 * i + 3]) * QSCALE);
            }
            qa[0] = p0[0]; qa[1] = p1[0]; qa[2] = p0[1]; qa[3] = p1[1];
            qa[4] = c < 2 ? p0[2] : 0u; qa[5] = c < 2 ? p1[2] : 0u;
            qb[0] = __shfl_xor_sync(~0u, c >= 2 ? p0[2] : p0[3], 2); qb[1] = __shfl_xor_sync(~0u, c >= 2 ? p1[2] : p1[3], 2);
            qb[2] = __shfl_xor_sync(~0u, c >= 2 ? p0[3] : p0[4], 2); qb[3] = __shfl_xor_sync(~0u, c >= 2 ? p1[3] : p1[4], 2);
            qb[4] = __shfl_xor_sync(~0u, c >= 2 ? p0[4] : 0u, 2); qb[5] = __shfl_xor_sync(~0u, c >= 2 ? p1[4] : 0u, 2);
        }
        PROF(1 + wg * 8);

        const uint64_t dK0 = mkdesc(sb + KVR_OFF, 128, 768, 0);
        const uint64_t dV0 = mkdesc(sb + KVR_OFF + 384, 768, 128, 0);
        const uint32_t qo_a = sb + QO_OFF + wg * 5120 + warp * 256 + r * 16 + c * 4;
        const uint32_t qo_b = sb + QO_OFF + wg * 5120 + warp * 256 + r * 16 + (c < 2 ? 2048 + 8 + c * 4 : 3072 + (c - 2) * 4);
#pragma unroll 1
        for (int pass = 0; pass < 2; pass++) {
            float sa[32], sbb[32], oa[12], ob[12];
            uint32_t pa[16], pb[16];
#pragma unroll
            for (int i = 0; i < 12; i++) { oa[i] = 0.f; ob[i] = 0.f; }
            mbar_wait(bars + B_KVFULL * 8, 0);
            PROF(6 + pass + wg * 8);
            wg_fence();
            QK0(sa, qa, dK0); QK1(sa, qa, dK0); QK0(sbb, qb, dK0); QK1(sbb, qb, dK0);
            wg_commit(); wg_wait<0>();
#pragma unroll
            for (int i = 0; i < 32; i++) asm volatile("" : "+f"(sa[i]), "+f"(sbb[i]) :: "memory");
            {
                float m0 = -INFINITY, m1 = -INFINITY, m2 = -INFINITY, m3 = -INFINITY;
#pragma unroll
                for (int j = 0; j < 8; j++) {
                    m0 = fmaxf(m0, fmaxf(sa[4 * j], sa[4 * j + 1])); m1 = fmaxf(m1, fmaxf(sa[4 * j + 2], sa[4 * j + 3]));
                    m2 = fmaxf(m2, fmaxf(sbb[4 * j], sbb[4 * j + 1])); m3 = fmaxf(m3, fmaxf(sbb[4 * j + 2], sbb[4 * j + 3]));
                }
#pragma unroll
                for (int o = 1; o < 4; o <<= 1) {
                    m0 = fmaxf(m0, __shfl_xor_sync(~0u, m0, o)); m1 = fmaxf(m1, __shfl_xor_sync(~0u, m1, o));
                    m2 = fmaxf(m2, __shfl_xor_sync(~0u, m2, o)); m3 = fmaxf(m3, __shfl_xor_sync(~0u, m3, o));
                }
                if (c == 2) {
                    qa[4] = pack_bf16(-(m0 + 80.f), 0.f); qa[5] = pack_bf16(-(m1 + 80.f), 0.f);
                    qb[4] = pack_bf16(-(m2 + 80.f), 0.f); qb[5] = pack_bf16(-(m3 + 80.f), 0.f);
                }
            }
            wg_fence();
            QK0(sa, qa, dK0); QK1(sa, qa, dK0);
            wg_commit(); wg_wait<0>();
            pb[12] = pb[13] = pb[14] = pb[15] = 0u;
            uint64_t dVp = dV0;
#pragma unroll 1
            for (int g = pass * 32; g < pass * 32 + 32; g++) {
                const uint64_t dK = dK0 + (g & 3) * 384, dV = dV0 + (g & 3) * 384;
                const int gn = g < 63 ? g + 1 : g;
                const uint64_t dKn = dK0 + (gn & 3) * 384;
                wg_fence(); PV(ob, pb, 3, dVp); wg_commit();
                chunk<0>(sa, pa);
                wg_fence(); QK0(sbb, qb, dK); PV(oa, pa, 0, dV); wg_commit();
                chunk<1>(sa, pa);
                wg_fence(); QK1(sbb, qb, dK); PV(oa, pa, 1, dV); wg_commit();
                chunk<2>(sa, pa);
                wg_fence(); PV(oa, pa, 2, dV); wg_commit();
                const bool nxt = mbar_try(bars + (B_KVFULL + (gn & 3)) * 8, (gn >> 2) & 1);
                chunk<3>(sa, pa);
                wg_wait<1>();
                mbar_arrive_if(bars + (B_KVEMPTY + ((g - 1) & 3)) * 8, lane == 0 && g > 0);
                wg_fence(); PV(oa, pa, 3, dV); wg_commit();
                chunk<0>(sbb, pb);
                if (!nxt) mbar_wait(bars + (B_KVFULL + (gn & 3)) * 8, (gn >> 2) & 1);
                wg_fence(); QK0(sa, qa, dKn); PV(ob, pb, 0, dV); wg_commit();
                chunk<1>(sbb, pb);
                wg_fence(); QK1(sa, qa, dKn); PV(ob, pb, 1, dV); wg_commit();
                chunk<2>(sbb, pb);
                wg_fence(); PV(ob, pb, 2, dV); wg_commit();
                chunk<3>(sbb, pb);
                wg_wait<1>();
                dVp = dV;
            }
            wg_fence(); PV(ob, pb, 3, dVp); wg_commit();
            wg_wait<0>();
#pragma unroll
            for (int i = 0; i < 12; i++) asm volatile("" : "+f"(oa[i]), "+f"(ob[i]) :: "memory");
            PROF(2 + pass * 2 + wg * 8);
            uint32_t na[6], nb[6];
            if (pass == 0) {
                mbar_wait(bars + B_Q2 * 8, 0);
                na[0] = lds32(qo_a); na[1] = lds32(qo_a + 128); na[2] = lds32(qo_a + 1024); na[3] = lds32(qo_a + 1152);
                na[4] = c < 2 ? lds32(qo_a + 2048) : 0u; na[5] = c < 2 ? lds32(qo_a + 2176) : 0u;
                nb[0] = lds32(qo_b); nb[1] = lds32(qo_b + 128); nb[2] = lds32(qo_b + 1024); nb[3] = lds32(qo_b + 1152);
                nb[4] = c < 2 ? lds32(qo_b + 2048) : 0u; nb[5] = c < 2 ? lds32(qo_b + 2176) : 0u;
                __syncwarp();
            } else {
                mbar_wait(bars + B_QOFREE * 8, 0);
#pragma unroll
                for (int i = 0; i < 6; i++) { na[i] = 0u; nb[i] = 0u; }
            }
            const int src = (lane & ~3) | 2;
            const float l0 = __shfl_sync(~0u, oa[8], src), l1 = __shfl_sync(~0u, oa[10], src);
            const float l2 = __shfl_sync(~0u, ob[8], src), l3 = __shfl_sync(~0u, ob[10], src);
            const float LO = 8.0779e-28f  , HI = 1.0e37f;
            bool ok = (l0 >= LO) && (l0 <= HI) && (l1 >= LO) && (l1 <= HI) && (l2 >= LO) && (l2 <= HI) && (l3 >= LO) && (l3 <= HI);
            float amax = 0.f;
#pragma unroll
            for (int i = 0; i < 12; i++) amax = amax + fabsf(oa[i]) * 0.03125f + fabsf(ob[i]) * 0.03125f;
            ok = ok && (amax <= 3.0e38f);
            if (__all_sync(~0u, ok)) {
                const float i0 = rcp(l0), i1 = rcp(l1), i2 = rcp(l2), i3 = rcp(l3);
                sts32(qo_a, pack_bf16(oa[0] * i0, oa[1] * i0)); sts32(qo_a + 128, pack_bf16(oa[2] * i1, oa[3] * i1));
                sts32(qo_a + 1024, pack_bf16(oa[4] * i0, oa[5] * i0)); sts32(qo_a + 1152, pack_bf16(oa[6] * i1, oa[7] * i1));
                sts32(qo_b, pack_bf16(ob[0] * i2, ob[1] * i2)); sts32(qo_b + 128, pack_bf16(ob[2] * i3, ob[3] * i3));
                sts32(qo_b + 1024, pack_bf16(ob[4] * i2, ob[5] * i2)); sts32(qo_b + 1152, pack_bf16(ob[6] * i3, ob[7] * i3));
                if (c < 2) {
                    sts32(qo_a + 2048, pack_bf16(oa[8] * i0, oa[9] * i0)); sts32(qo_a + 2176, pack_bf16(oa[10] * i1, oa[11] * i1));
                    sts32(qo_b + 2048, pack_bf16(ob[8] * i2, ob[9] * i2)); sts32(qo_b + 2176, pack_bf16(ob[10] * i3, ob[11] * i3));
                }
            } else {
                sts32(qo_a, qa[0]); sts32(qo_a + 128, qa[1]); sts32(qo_a + 1024, qa[2]); sts32(qo_a + 1152, qa[3]);
                sts32(qo_b, qb[0]); sts32(qo_b + 128, qb[1]); sts32(qo_b + 1024, qb[2]); sts32(qo_b + 1152, qb[3]);
                if (c < 2) { sts32(qo_a + 2048, qa[4]); sts32(qo_a + 2176, qa[5]); sts32(qo_b + 2048, qb[4]); sts32(qo_b + 2176, qb[5]); }
                __syncwarp();
                mbar_wait(bars + B_KVALL * 8, 0);
                attn_exact_row(sb + QO_OFF, warp * 16 + (lane & 15), wg * 40 + (lane >> 4) * 20);
            }
            fence_async_smem();
            __syncwarp();
            if (lane == 0) mbar_arrive(bars + B_OREADY * 8);
#pragma unroll
            for (int i = 0; i < 6; i++) { qa[i] = na[i]; qb[i] = nb[i]; }
            PROF(3 + pass * 2 + wg * 8);
        }
    } else if (wg == 2) {
        asm volatile("setmaxnreg.inc.sync.aligned.u32 168;");
        const uint64_t dXN = mkdesc(sb + XN_OFF, 16, 1024, 1);
        {
            float d[8];
            const uint64_t dB = mkdesc(sb + KVR_OFF, 256, 128, 0);
            wg_fence();
#pragma unroll
            for (int kc = 0; kc < 10; kc++) {
#pragma unroll
                for (int k = 0; k < 4; k++) wgmma_ss_n16(d, dXN + kc * 512 + k * 2, dB + kc * 128 + k * 32, (kc | k) != 0);
            }
            wg_commit();
            asm volatile("bar.arrive 2, 384;" ::: "memory");
            wg_wait<0>();
#pragma unroll
            for (int i = 0; i < 8; i++) asm volatile("" : "+f"(d[i]) :: "memory");
            char* kvb = (char*)g_kv + rb * 6144 + warp * 1536 + (cb >> 1) * 384 + r * 16;
            const int d0 = (cb & 1) * 10 + 2 * c, d1 = d0 + 8;
            *(uint32_t*)(kvb + (d0 >> 3) * 128 + (d0 & 7) * 2) = pack_bf16(d[0], d[1]);
            *(uint32_t*)(kvb + 768 + (d0 >> 3) * 128 + (d0 & 7) * 2) = pack_bf16(d[2], d[3]);
            if (c == 0 || ((cb & 1) && c < 3)) {
                const uint32_t cst = c == 1 ? 0x00003F80u : 0u;
                *(uint32_t*)(kvb + (d1 >> 3) * 128 + (d1 & 7) * 2) = c == 0 ? pack_bf16(d[4], d[5]) : cst;
                *(uint32_t*)(kvb + 768 + (d1 >> 3) * 128 + (d1 & 7) * 2) = c == 0 ? pack_bf16(d[6], d[7]) : cst;
            }
            PROF(16);
            fence_async_glob();
            __syncwarp();
            if (lane == 0) red_release(&g_flag_kv[rb]);
        }
        PROF(17);
        {
            float d[40];
#pragma unroll 1
            for (int s = 0; s < 5; s++) {
                const int sl = s % 3;
                mbar_wait(bars + (B_RING + sl) * 8, (s / 3) & 1);
                const uint64_t dB = mkdesc(sb + RING_OFF + sl * 32768, 4096, 512, 2);
#pragma unroll
                for (int k = 0; k < 8; k += 2) {
                    wg_fence();
                    wgmma_ss_n80(d, dXN + (2 * s + (k >> 2)) * 512 + (k & 3) * 2, dB + (k >> 2) * 768 + (k & 3) * 64, (s | k) != 0);
                    wgmma_ss_n80(d, dXN + (2 * s + (k >> 2)) * 512 + (k & 3) * 2 + 2, dB + (k >> 2) * 768 + (k & 3) * 64 + 64, 1);
                    wg_commit(); wg_wait<0>();
                }
                mbar_arrive_if(bars + (B_REMPTY + sl) * 8, lane == 0);
            }
#pragma unroll
            for (int i = 0; i < 40; i++) asm volatile("" : "+f"(d[i]) :: "memory");
            const uint32_t qa_ = sb + QO_OFF + warp * 256 + r * 16 + c * 4;
#pragma unroll
            for (int j = 0; j < 10; j++) {
                sts32(qa_ + j * 1024, pack_bf16(d[4 * j] * QSCALE, d[4 * j + 1] * QSCALE));
                sts32(qa_ + j * 1024 + 128, pack_bf16(d[4 * j + 2] * QSCALE, d[4 * j + 3] * QSCALE));
            }
            __syncwarp();
            if (lane == 0) mbar_arrive(bars + B_Q2 * 8);
        }
        PROF(18);
        int sl = 2, ph = 1;
#pragma unroll 1
        for (int jj = 0; jj < 3; jj++) {
            float d[64], e[64];
#pragma unroll 1
            for (int kc = 0; kc < 10; kc++) {
                mbar_wait(bars + (B_RING + sl) * 8, ph);
                const uint64_t dB = mkdesc(sb + RING_OFF + sl * 32768, 8192, 1024, 1);
#pragma unroll
                for (int k = 0; k < 4; k++) {
                    wg_fence();
                    wgmma_ss_n128(d, dXN + kc * 512 + k * 2, dB + k * 128, (kc | k) != 0);
                    wgmma_ss_n128(e, dXN + kc * 512 + k * 2, dB + 1024 + k * 128, (kc | k) != 0);
                    wg_commit(); wg_wait<0>();
                }
                mbar_arrive_if(bars + (B_REMPTY + sl) * 8, lane == 0);
                if (++sl == 3) { sl = 0; ph ^= 1; }
            }
#pragma unroll
            for (int i = 0; i < 64; i++) asm volatile("" : "+f"(d[i]), "+f"(e[i]) :: "memory");
            mbar_wait(bars + B_HFREE * 8, (jj & 1) ^ 1);
            const int mrow = warp * 16 + ((lane >> 3) & 1) * 8 + (lane & 7);
            const uint32_t ha = sb + HST_OFF + mrow * 128;
#pragma unroll
            for (int j = 0; j < 16; j += 2) {
                uint32_t h[4];
#pragma unroll
                for (int i = 0; i < 4; i++)
                    h[i] = bf2_mul(pack_bf16(d[4 * j + 2 * i], d[4 * j + 2 * i + 1]), pack_bf16(e[4 * j + 2 * i], e[4 * j + 2 * i + 1]));
                const int blk = (j & 7) + (lane >> 4);
                stsm4(ha + (j >> 3) * 8192 + ((blk ^ (mrow & 7)) << 4), h[0], h[1], h[2], h[3]);
            }
            fence_async_smem();
            __syncwarp();
            if (lane == 0) mbar_arrive(bars + B_HFULL * 8);
            PROF(19 + jj);
        }
        uint32_t gs[40];
        {
            float d[80];
#pragma unroll 1
            for (int kc = 0; kc < 24; kc++) {
                mbar_wait(bars + (B_RING + sl) * 8, ph);
                const uint64_t dA = mkdesc(sb + RING_OFF + sl * 32768, 16, 1024, 1);
                const uint64_t dB = mkdesc(sb + RING_OFF + sl * 32768 + 8192, 4096, 512, 2);
#pragma unroll
                for (int k = 0; k < 4; k++) {
                    wg_fence();
                    wgmma_ss_n160(d, dA + k * 2, dB + k * 64, (kc | k) != 0);
                    wg_commit(); wg_wait<0>();
                }
                mbar_arrive_if(bars + (B_REMPTY + sl) * 8, lane == 0);
                if (++sl == 3) { sl = 0; ph ^= 1; }
            }
#pragma unroll
            for (int i = 0; i < 80; i++) asm volatile("" : "+f"(d[i]) :: "memory");
#pragma unroll
            for (int i = 0; i < 40; i++) {
                const uint32_t y2 = pack_bf16(d[2 * i], d[2 * i + 1]);
                const float y0 = bf_lo(y2), y1 = bf_hi(y2);
                gs[i] = pack_bf16(y0 * rcp(1.0f + ex2(y0 * -1.4426950408889634f)), y1 * rcp(1.0f + ex2(y1 * -1.4426950408889634f)));
            }
        }
        PROF(22);
        {
            float d[80];
            mbar_wait(bars + B_OBLOB * 8, 0);
#pragma unroll 1
            for (int i = 0; i < 4; i++) {
                mbar_wait(bars + (B_WO + i) * 8, 0);
                const uint64_t dA = mkdesc(sb + XN_OFF + i * 10240, 1024, 128, 0);
                const uint64_t dB = mkdesc(sb + RING_OFF + i * 25600, 5120, 512, 2);
#pragma unroll
                for (int k = 0; k < 5; k++) {
                    wg_fence();
                    wgmma_ss_n160(d, dA + k * 128, dB + k * 64, (i | k) != 0);
                    wg_commit(); wg_wait<0>();
                }
            }
            mbar_arrive_if(bars + B_WODONE * 8, lane == 0);
            PROF(23);
#pragma unroll
            for (int i = 0; i < 4; i++) mbar_wait(bars + (B_WO + i) * 8, 1);
            mbar_wait(bars + B_XT * 8, 0);
            const uint64_t dB = mkdesc(sb + RING_OFF, 5120, 512, 2);
            mbar_wait(bars + B_OREADY * 8, 1);
            PROF(28);
            {
                const uint64_t dA = mkdesc(sb + QO_OFF, 1024, 128, 0);
                wg_fence();
#pragma unroll
                for (int k = 0; k < 5; k++) wgmma_ss_n160(d, dA + k * 128, dB + k * 64, 1);
                wg_commit();
            }
            mbar_wait(bars + B_OBLOB * 8, 1);
            PROF(29);
            {
                const uint64_t dA = mkdesc(sb + XN_OFF, 1024, 128, 0);
                wg_fence();
#pragma unroll
                for (int k = 5; k < 20; k++) wgmma_ss_n160(d, dA + (k / 5) * 640 + (k % 5) * 128, dB + (k / 5) * 1600 + (k % 5) * 64, 1);
                wg_commit();
            }
            wg_wait<0>();
#pragma unroll
            for (int i = 0; i < 80; i++) asm volatile("" : "+f"(d[i]) :: "memory");
            PROF(30);
            const int mrow = warp * 16 + ((lane >> 3) & 1) * 8 + (lane & 7);
            const uint32_t xa = sb + XT_OFF + mrow * 336 + (lane >> 4) * 16;
#pragma unroll
            for (int j = 0; j < 20; j += 2) {
                uint32_t x[4];
                ldsm4(xa + j * 16, x[0], x[1], x[2], x[3]);
#pragma unroll
                for (int i = 0; i < 4; i++)
                    x[i] = bf2_add(x[i], bf2_mul(pack_bf16(d[4 * j + 2 * i], d[4 * j + 2 * i + 1]), gs[2 * j + i]));
                stsm4(xa + j * 16, x[0], x[1], x[2], x[3]);
            }
            fence_async_smem();
            __syncwarp();
            if (lane < 16) {
                const int row = warp * 16 + lane;
                bulk_store(P.out + (size_t)(rb * 64 + row) * 640 + cb * 160, sb + XT_OFF + row * 336, 320);
                bulk_commit_wait();
            }
            PROF(31);
        }
    } else {
        asm volatile("setmaxnreg.dec.sync.aligned.u32 40;");
        if (warp == 0) {
            const int tile = (rb + lane) & 31;
            bool seen = false, issued = lane >= 4;
            for (uint32_t it = 0;; it++) {
                if (!seen) seen = (int)(ld_acquire(&g_flag_kv[tile]) - epoch * 16u) >= 0;
                const uint32_t m = __ballot_sync(~0u, seen);
                if (!issued && seen && (m & 1u)) {
                    issued = true;
                    fence_async_glob();
                    mbar_expect_tx(bars + (B_KVFULL + lane) * 8, 6144);
                    bulk_load(sb + KVR_OFF + lane * 6144, (const char*)g_kv + tile * 6144, 6144, bars + (B_KVFULL + lane) * 8);
                }
                if (m == ~0u) break;
                if (it > 4000000u) __trap();
            }
            fence_async_glob();
            __syncwarp();
            if (lane == 0) {
                mbar_arrive(bars + B_KVALL * 8);
                for (int g = 4; g < 64; g++) {
                    mbar_wait(bars + (B_KVEMPTY + (g & 3)) * 8, ((g >> 2) - 1) & 1);
                    mbar_expect_tx(bars + (B_KVFULL + (g & 3)) * 8, 6144);
                    bulk_load(sb + KVR_OFF + (g & 3) * 6144, (const char*)g_kv + ((rb + g) & 31) * 6144, 6144, bars + (B_KVFULL + (g & 3)) * 8);
                }
            }
        } else if (warp == 1) {
            if (lane == 0) {
                mbar_wait(bars + B_SLABFREE * 8, 0);
                int sl = 0, ph = 1;
                for (int s = 0; s < 59; s++) {
                    mbar_wait(bars + (B_REMPTY + sl) * 8, ph);
                    const uint32_t slot = sb + RING_OFF + sl * 32768, bar = bars + (B_RING + sl) * 8;
                    if (s < 5) {
                        mbar_expect_tx(bar, 24576);
                        for (int i = 0; i < 6; i++) tma2d(slot + i * 4096, &tm_wq, cb * 160 + 80 + 32 * (i % 3), (2 * s + i / 3) * 64, bar);
                    } else if (s < 35) {
                        const int jj = (s - 5) / 10, kc = (s - 5) % 10;
                        mbar_expect_tx(bar, 32768);
                        tma3d(slot, &tm_wg, 0, kc * 64, cb * 6 + jj * 2, bar);
                        tma3d(slot + 16384, &tm_wu, 0, kc * 64, cb * 6 + jj * 2, bar);
                    } else {
                        const int kc = s - 35;
                        mbar_expect_tx(bar, 28672);
                        tma3d(slot + 8192, &tm_wd, 0, kc * 64, cb * 5, bar);
                        if (s == 35) { flag_wait(&g_flag_h[rb], epoch * 12u); fence_async_glob(); }
                        bulk_load(slot, (const char*)g_h + (size_t)(rb * 24 + kc) * 8192, 8192, bar);
                    }
                    if (++sl == 3) { sl = 0; ph ^= 1; }
                }
                for (int s = 0; s < 3; s++) {
                    mbar_wait(bars + (B_REMPTY + sl) * 8, ph);
                    if (++sl == 3) { sl = 0; ph ^= 1; }
                }
                for (int pass = 0; pass < 2; pass++) {
                    if (pass) mbar_wait(bars + B_WODONE * 8, 0);
                    for (int i = 0; i < 4; i++) {
                        mbar_expect_tx(bars + (B_WO + i) * 8, 25600);
                        tma3d(sb + RING_OFF + i * 25600, &tm_wo, 0, ((cb + i) & 3) * 160 + pass * 80, cb * 5, bars + (B_WO + i) * 8);
                    }
                }
            }
        } else if (warp == 2) {
            if (lane == 0) {
                for (int jj = 0; jj < 3; jj++) {
                    mbar_wait(bars + B_HFULL * 8, jj & 1);
                    bulk_store((char*)g_h + (size_t)(rb * 24 + cb * 6 + jj * 2) * 8192, sb + HST_OFF, 16384);
                    bulk_commit_wait();
                    fence_async_glob();
                    red_release(&g_flag_h[rb]);
                    mbar_arrive(bars + B_HFREE * 8);
                }
                mbar_expect_tx(bars + B_XT * 8, 64 * 320);
                for (int i = 0; i < 64; i++) bulk_load(sb + XT_OFF + i * 336, P.x + (size_t)(rb * 64 + i) * 640 + cb * 160, 320, bars + B_XT * 8);
                for (int pass = 0; pass < 2; pass++) {
                    mbar_wait(bars + B_OREADY * 8, pass);
                    bulk_store((char*)g_o + (size_t)(rb * 8 + pass * 4 + cb) * 10240, sb + QO_OFF, 10240);
                    bulk_commit_wait();
                    fence_async_glob();
                    red_release(&g_flag_o[rb * 2 + pass]);
                    if (pass == 0) mbar_arrive(bars + B_QOFREE * 8);
                    else mbar_wait(bars + B_WODONE * 8, 0);
                    mbar_expect_tx(bars + B_OBLOB * 8, pass ? 30720 : 40960);
                    flag_wait(&g_flag_o[rb * 2 + pass], epoch * 4u);
                    fence_async_glob();
                    for (int i = pass; i < 4; i++)
                        bulk_load(sb + XN_OFF + i * 10240, (const char*)g_o + (size_t)(rb * 8 + pass * 4 + ((cb + i) & 3)) * 10240, 10240, bars + B_OBLOB * 8);
                }
                g_epoch[bid] = epoch;
            }
        } else {
            if (lane == 0) {
                l2_prefetch((const char*)P.wq + bid * 6400, 6400);
                mbar_wait(bars + B_KVALL * 8, 0);
                l2_prefetch((const char*)P.wg + bid * 15360, 15360);
                l2_prefetch((const char*)P.wu + bid * 15360, 15360);
                l2_prefetch((const char*)P.wd + bid * 15360, 15360);
                l2_prefetch((const char*)P.wo + bid * 6400, 6400);
            }
        }
    }
}

typedef CUresult (*EncodeFn)(CUtensorMap*, CUtensorMapDataType, cuuint32_t, void*, const cuuint64_t*, const cuuint64_t*, const cuuint32_t*,
                             const cuuint32_t*, CUtensorMapInterleave, CUtensorMapSwizzle, CUtensorMapL2promotion, CUtensorMapFloatOOBfill);

static void make_map(EncodeFn enc, CUtensorMap* m, const void* base, int K, int N, int grp, int boxk, int ngrp, CUtensorMapSwizzle sw) {
    cuuint32_t es[3] = {1, 1, 1};
    if (ngrp == 0) {
        cuuint64_t dims[2] = {(cuuint64_t)N, (cuuint64_t)K};
        cuuint64_t str[1] = {(cuuint64_t)N * 2};
        cuuint32_t box[2] = {(cuuint32_t)grp, (cuuint32_t)boxk};
        enc(m, CU_TENSOR_MAP_DATA_TYPE_BFLOAT16, 2, (void*)base, dims, str, box, es, CU_TENSOR_MAP_INTERLEAVE_NONE, sw,
            CU_TENSOR_MAP_L2_PROMOTION_L2_128B, CU_TENSOR_MAP_FLOAT_OOB_FILL_NONE);
    } else {
        cuuint64_t dims[3] = {(cuuint64_t)grp, (cuuint64_t)K, (cuuint64_t)(N / grp)};
        cuuint64_t str[2] = {(cuuint64_t)N * 2, (cuuint64_t)grp * 2};
        cuuint32_t box[3] = {(cuuint32_t)grp, (cuuint32_t)boxk, (cuuint32_t)ngrp};
        enc(m, CU_TENSOR_MAP_DATA_TYPE_BFLOAT16, 3, (void*)base, dims, str, box, es, CU_TENSOR_MAP_INTERLEAVE_NONE, sw,
            CU_TENSOR_MAP_L2_PROMOTION_L2_128B, CU_TENSOR_MAP_FLOAT_OOB_FILL_NONE);
    }
}

}

extern "C" void kernel_launch(void* const* d_in, const int* in_sizes, int n_in, void* d_out, int out_size) {
    using namespace mk;
    void* fn = nullptr;
    cudaDriverEntryPointQueryResult qr;
    cudaGetDriverEntryPoint("cuTensorMapEncodeTiled", &fn, cudaEnableDefault, &qr);
    EncodeFn enc = (EncodeFn)fn;
    Params P;
    P.x = (const __nv_bfloat16*)d_in[0]; P.wq = (const __nv_bfloat16*)d_in[1]; P.wk = (const __nv_bfloat16*)d_in[2];
    P.wv = (const __nv_bfloat16*)d_in[3]; P.wo = (const __nv_bfloat16*)d_in[4]; P.wg = (const __nv_bfloat16*)d_in[6];
    P.wu = (const __nv_bfloat16*)d_in[7]; P.wd = (const __nv_bfloat16*)d_in[8]; P.out = (__nv_bfloat16*)d_out;
    CUtensorMap tq, tg, tu, td, to;
    make_map(enc, &tq, P.wq, 640, 640, 32, 64, 0, CU_TENSOR_MAP_SWIZZLE_64B);
    make_map(enc, &tg, P.wg, 640, 1536, 64, 64, 2, CU_TENSOR_MAP_SWIZZLE_128B);
    make_map(enc, &tu, P.wu, 640, 1536, 64, 64, 2, CU_TENSOR_MAP_SWIZZLE_128B);
    make_map(enc, &td, P.wd, 1536, 640, 32, 64, 5, CU_TENSOR_MAP_SWIZZLE_64B);
    make_map(enc, &to, P.wo, 640, 640, 32, 80, 5, CU_TENSOR_MAP_SWIZZLE_64B);
    cudaFuncSetAttribute(fused_kernel, cudaFuncAttributeMaxDynamicSharedMemorySize, SMEM_TOTAL);
    fused_kernel<<<128, 512, SMEM_TOTAL, cudaStreamPerThread>>>(tq, tg, tu, td, to, P);
}
```

```cpp
#include <cuda_runtime.h>
#include <cuda_bf16.h>
#include <cuda.h>
#include <stdint.h>

#define PMASK 0x11011101u
#define SLAB_DELAY 1800u
#define PDEG 4

namespace mk {

constexpr uint32_t XN_OFF = 0, RING_OFF = 81920, HST_OFF = 180224, QO_OFF = 196608, KVR_OFF = 206848, BAR_OFF = 231424,
                   SMEM_TOTAL = 232448;
constexpr uint32_t WRAW_OFF = 204800, WKV_OFF = RING_OFF + 92160;
constexpr uint32_t XT_OFF = XN_OFF + 40960;
enum { B_SLAB = 0, B_SLABFREE = 1, B_KVFULL = 2, B_KVALL = 6, B_RING = 7, B_Q2 = 10, B_OREADY = 11, B_QOFREE = 12,
       B_WO = 13, B_OBLOB = 17, B_XT = 18, B_KVEMPTY = 19, B_REMPTY = 23, B_HFULL = 26, B_HFREE = 27, B_WODONE = 28, B_WKV = 29, B_SLAB2 = 30, NBAR = 31 };

struct Scratch {
    uint4 kv[32 * 6144 / 16];
    uint4 h[32 * 24 * 8192 / 16];
    uint4 o[32 * 8 * 10240 / 16];
    unsigned flag_kv[32], flag_h[32], flag_o[64], epoch[128];
};
__device__ __align__(1024) Scratch g_scratch;
#define g_kv (P.s->kv)
#define g_h (P.s->h)
#define g_o (P.s->o)
#define g_flag_kv (P.s->flag_kv)
#define g_flag_h (P.s->flag_h)
#define g_flag_o (P.s->flag_o)
#define g_epoch (P.s->epoch)
#define PROF(i)
#define PROFW(i)
#define PROFV(i, v)
#define PW_BEGIN()
#define PW_END(acc)

__device__ __forceinline__ void wgmma_rs_n24_t1(float (&d)[12], uint32_t a0, uint32_t a1, uint32_t a2, uint32_t a3, uint64_t desc, int scale_d) {
    asm volatile("{\n.reg .pred p;\nsetp.ne.b32 p, %17, 0;\n"
        "wgmma.mma_async.sync.aligned.m64n24k16.f32.bf16.bf16 {%0, %1, %2, %3, %4, %5, %6, %7, %8, %9, %10, %11}, {%12, %13, %14, %15}, %16, p, 1, 1, 1;\n}\n"
        : "+f"(d[0]), "+f"(d[1]), "+f"(d[2]), "+f"(d[3]), "+f"(d[4]), "+f"(d[5]), "+f"(d[6]), "+f"(d[7]), "+f"(d[8]), "+f"(d[9]), "+f"(d[10]), "+f"(d[11])
        : "r"(a0), "r"(a1), "r"(a2), "r"(a3), "l"(desc), "r"(scale_d));
}
__device__ __forceinline__ void wgmma_rs_n64_t0(float (&d)[32], uint32_t a0, uint32_t a1, uint32_t a2, uint32_t a3, uint64_t desc, int scale_d) {
    asm volatile("{\n.reg .pred p;\nsetp.ne.b32 p, %37, 0;\n"
        "wgmma.mma_async.sync.aligned.m64n64k16.f32.bf16.bf16 {%0, %1, %2, %3, %4, %5, %6, %7, %8, %9, %10, %11, %12, %13, %14, %15, %16, %17, %18, %19, %20, %21, %22, %23, %24, %25, %26, %27, %28, %29, %30, %31}, {%32, %33, %34, %35}, %36, p, 1, 1, 0;\n}\n"
        : "+f"(d[0]), "+f"(d[1]), "+f"(d[2]), "+f"(d[3]), "+f"(d[4]), "+f"(d[5]), "+f"(d[6]), "+f"(d[7]), "+f"(d[8]), "+f"(d[9]), "+f"(d[10]), "+f"(d[11]), "+f"(d[12]), "+f"(d[13]), "+f"(d[14]), "+f"(d[15]), "+f"(d[16]), "+f"(d[17]), "+f"(d[18]), "+f"(d[19]), "+f"(d[20]), "+f"(d[21]), "+f"(d[22]), "+f"(d[23]), "+f"(d[24]), "+f"(d[25]), "+f"(d[26]), "+f"(d[27]), "+f"(d[28]), "+f"(d[29]), "+f"(d[30]), "+f"(d[31])
        : "r"(a0), "r"(a1), "r"(a2), "r"(a3), "l"(desc), "r"(scale_d));
}
__device__ __forceinline__ void wgmma_ss_n24(float (&d)[12], uint64_t da, uint64_t db, int scale_d) {
    asm volatile("{\n.reg .pred p;\nsetp.ne.b32 p, %14, 0;\n"
        "wgmma.mma_async.sync.aligned.m64n24k16.f32.bf16.bf16 {%0, %1, %2, %3, %4, %5, %6, %7, %8, %9, %10, %11}, %12, %13, p, 1, 1, 0, 1;\n}\n"
        : "+f"(d[0]), "+f"(d[1]), "+f"(d[2]), "+f"(d[3]), "+f"(d[4]), "+f"(d[5]), "+f"(d[6]), "+f"(d[7]), "+f"(d[8]), "+f"(d[9]), "+f"(d[10]), "+f"(d[11])
        : "l"(da), "l"(db), "r"(scale_d));
}
__device__ __forceinline__ void wgmma_ss_n48(float (&d)[24], uint64_t da, uint64_t db, int scale_d) {
    asm volatile("{\n.reg .pred p;\nsetp.ne.b32 p, %26, 0;\n"
        "wgmma.mma_async.sync.aligned.m64n48k16.f32.bf16.bf16 {%0, %1, %2, %3, %4, %5, %6, %7, %8, %9, %10, %11, %12, %13, %14, %15, %16, %17, %18, %19, %20, %21, %22, %23}, %24, %25, p, 1, 1, 0, 1;\n}\n"
        : "+f"(d[0]), "+f"(d[1]), "+f"(d[2]), "+f"(d[3]), "+f"(d[4]), "+f"(d[5]), "+f"(d[6]), "+f"(d[7]), "+f"(d[8]), "+f"(d[9]), "+f"(d[10]), "+f"(d[11]), "+f"(d[12]), "+f"(d[13]), "+f"(d[14]), "+f"(d[15]), "+f"(d[16]), "+f"(d[17]), "+f"(d[18]), "+f"(d[19]), "+f"(d[20]), "+f"(d[21]), "+f"(d[22]), "+f"(d[23])
        : "l"(da), "l"(db), "r"(scale_d));
}
__device__ __forceinline__ void wgmma_ss_n80(float (&d)[40], uint64_t da, uint64_t db, int scale_d) {
    asm volatile("{\n.reg .pred p;\nsetp.ne.b32 p, %42, 0;\n"
        "wgmma.mma_async.sync.aligned.m64n80k16.f32.bf16.bf16 {%0, %1, %2, %3, %4, %5, %6, %7, %8, %9, %10, %11, %12, %13, %14, %15, %16, %17, %18, %19, %20, %21, %22, %23, %24, %25, %26, %27, %28, %29, %30, %31, %32, %33, %34, %35, %36, %37, %38, %39}, %40, %41, p, 1, 1, 0, 1;\n}\n"
        : "+f"(d[0]), "+f"(d[1]), "+f"(d[2]), "+f"(d[3]), "+f"(d[4]), "+f"(d[5]), "+f"(d[6]), "+f"(d[7]), "+f"(d[8]), "+f"(d[9]), "+f"(d[10]), "+f"(d[11]), "+f"(d[12]), "+f"(d[13]), "+f"(d[14]), "+f"(d[15]), "+f"(d[16]), "+f"(d[17]), "+f"(d[18]), "+f"(d[19]), "+f"(d[20]), "+f"(d[21]), "+f"(d[22]), "+f"(d[23]), "+f"(d[24]), "+f"(d[25]), "+f"(d[26]), "+f"(d[27]), "+f"(d[28]), "+f"(d[29]), "+f"(d[30]), "+f"(d[31]), "+f"(d[32]), "+f"(d[33]), "+f"(d[34]), "+f"(d[35]), "+f"(d[36]), "+f"(d[37]), "+f"(d[38]), "+f"(d[39])
        : "l"(da), "l"(db), "r"(scale_d));
}
__device__ __forceinline__ void wgmma_ss_n128(float (&d)[64], uint64_t da, uint64_t db, int scale_d) {
    asm volatile("{\n.reg .pred p;\nsetp.ne.b32 p, %66, 0;\n"
        "wgmma.mma_async.sync.aligned.m64n128k16.f32.bf16.bf16 {%0, %1, %2, %3, %4, %5, %6, %7, %8, %9, %10, %11, %12, %13, %14, %15, %16, %17, %18, %19, %20, %21, %22, %23, %24, %25, %26, %27, %28, %29, %30, %31, %32, %33, %34, %35, %36, %37, %38, %39, %40, %41, %42, %43, %44, %45, %46, %47, %48, %49, %50, %51, %52, %53, %54, %55, %56, %57, %58, %59, %60, %61, %62, %63}, %64, %65, p, 1, 1, 0, 1;\n}\n"
        : "+f"(d[0]), "+f"(d[1]), "+f"(d[2]), "+f"(d[3]), "+f"(d[4]), "+f"(d[5]), "+f"(d[6]), "+f"(d[7]), "+f"(d[8]), "+f"(d[9]), "+f"(d[10]), "+f"(d[11]), "+f"(d[12]), "+f"(d[13]), "+f"(d[14]), "+f"(d[15]), "+f"(d[16]), "+f"(d[17]), "+f"(d[18]), "+f"(d[19]), "+f"(d[20]), "+f"(d[21]), "+f"(d[22]), "+f"(d[23]), "+f"(d[24]), "+f"(d[25]), "+f"(d[26]), "+f"(d[27]), "+f"(d[28]), "+f"(d[29]), "+f"(d[30]), "+f"(d[31]), "+f"(d[32]), "+f"(d[33]), "+f"(d[34]), "+f"(d[35]), "+f"(d[36]), "+f"(d[37]), "+f"(d[38]), "+f"(d[39]), "+f"(d[40]), "+f"(d[41]), "+f"(d[42]), "+f"(d[43]), "+f"(d[44]), "+f"(d[45]), "+f"(d[46]), "+f"(d[47]), "+f"(d[48]), "+f"(d[49]), "+f"(d[50]), "+f"(d[51]), "+f"(d[52]), "+f"(d[53]), "+f"(d[54]), "+f"(d[55]), "+f"(d[56]), "+f"(d[57]), "+f"(d[58]), "+f"(d[59]), "+f"(d[60]), "+f"(d[61]), "+f"(d[62]), "+f"(d[63])
        : "l"(da), "l"(db), "r"(scale_d));
}
__device__ __forceinline__ void wgmma_ss_n160(float (&d)[80], uint64_t da, uint64_t db, int scale_d) {
    asm volatile("{\n.reg .pred p;\nsetp.ne.b32 p, %82, 0;\n"
        "wgmma.mma_async.sync.aligned.m64n160k16.f32.bf16.bf16 {%0, %1, %2, %3, %4, %5, %6, %7, %8, %9, %10, %11, %12, %13, %14, %15, %16, %17, %18, %19, %20, %21, %22, %23, %24, %25, %26, %27, %28, %29, %30, %31, %32, %33, %34, %35, %36, %37, %38, %39, %40, %41, %42, %43, %44, %45, %46, %47, %48, %49, %50, %51, %52, %53, %54, %55, %56, %57, %58, %59, %60, %61, %62, %63, %64, %65, %66, %67, %68, %69, %70, %71, %72, %73, %74, %75, %76, %77, %78, %79}, %80, %81, p, 1, 1, 0, 1;\n}\n"
        : "+f"(d[0]), "+f"(d[1]), "+f"(d[2]), "+f"(d[3]), "+f"(d[4]), "+f"(d[5]), "+f"(d[6]), "+f"(d[7]), "+f"(d[8]), "+f"(d[9]), "+f"(d[10]), "+f"(d[11]), "+f"(d[12]), "+f"(d[13]), "+f"(d[14]), "+f"(d[15]), "+f"(d[16]), "+f"(d[17]), "+f"(d[18]), "+f"(d[19]), "+f"(d[20]), "+f"(d[21]), "+f"(d[22]), "+f"(d[23]), "+f"(d[24]), "+f"(d[25]), "+f"(d[26]), "+f"(d[27]), "+f"(d[28]), "+f"(d[29]), "+f"(d[30]), "+f"(d[31]), "+f"(d[32]), "+f"(d[33]), "+f"(d[34]), "+f"(d[35]), "+f"(d[36]), "+f"(d[37]), "+f"(d[38]), "+f"(d[39]), "+f"(d[40]), "+f"(d[41]), "+f"(d[42]), "+f"(d[43]), "+f"(d[44]), "+f"(d[45]), "+f"(d[46]), "+f"(d[47]), "+f"(d[48]), "+f"(d[49]), "+f"(d[50]), "+f"(d[51]), "+f"(d[52]), "+f"(d[53]), "+f"(d[54]), "+f"(d[55]), "+f"(d[56]), "+f"(d[57]), "+f"(d[58]), "+f"(d[59]), "+f"(d[60]), "+f"(d[61]), "+f"(d[62]), "+f"(d[63]), "+f"(d[64]), "+f"(d[65]), "+f"(d[66]), "+f"(d[67]), "+f"(d[68]), "+f"(d[69]), "+f"(d[70]), "+f"(d[71]), "+f"(d[72]), "+f"(d[73]), "+f"(d[74]), "+f"(d[75]), "+f"(d[76]), "+f"(d[77]), "+f"(d[78]), "+f"(d[79])
        : "l"(da), "l"(db), "r"(scale_d));
}

__device__ __forceinline__ uint32_t smem_u32(const void* p) { return (uint32_t)__cvta_generic_to_shared(p); }
__device__ __forceinline__ void wg_fence() { asm volatile("wgmma.fence.sync.aligned;" ::: "memory"); }
__device__ __forceinline__ void wg_commit() { asm volatile("wgmma.commit_group.sync.aligned;" ::: "memory"); }
template <int N> __device__ __forceinline__ void wg_wait() { asm volatile("wgmma.wait_group.sync.aligned %0;" :: "n"(N) : "memory"); }
__device__ __forceinline__ uint64_t mkdesc(uint32_t addr, uint32_t lbo, uint32_t sbo, uint32_t mode) {
    return (uint64_t)((addr & 0x3FFFF) >> 4) | ((uint64_t)(lbo >> 4) << 16) | ((uint64_t)(sbo >> 4) << 32) | ((uint64_t)mode << 62);
}
__device__ __forceinline__ void mbar_init(uint32_t bar, int cnt) { asm volatile("mbarrier.init.shared::cta.b64 [%0], %1;" :: "r"(bar), "r"(cnt) : "memory"); }
__device__ __forceinline__ void mbar_expect_tx(uint32_t bar, uint32_t bytes) { asm volatile("mbarrier.arrive.expect_tx.shared::cta.b64 _, [%0], %1;" :: "r"(bar), "r"(bytes) : "memory"); }
__device__ __forceinline__ void mbar_arrive(uint32_t bar) { asm volatile("mbarrier.arrive.shared::cta.b64 _, [%0];" :: "r"(bar) : "memory"); }
__device__ __forceinline__ bool mbar_try(uint32_t bar, uint32_t parity) {
    uint32_t ok;
    asm volatile("{\n.reg .pred p;\nmbarrier.try_wait.parity.shared::cta.b64 p, [%1], %2;\nselp.b32 %0, 1, 0, p;\n}" : "=r"(ok) : "r"(bar), "r"(parity) : "memory");
    return ok != 0;
}
__device__ __forceinline__ void mbar_wait(uint32_t bar, uint32_t parity) {
    asm volatile("{\n.reg .pred p;\n.reg .u32 n;\nmov.u32 n, 0;\n"
                 "WL:\nmbarrier.try_wait.parity.shared::cta.b64 p, [%0], %1;\n@p bra WD;\n"
                 "add.u32 n, n, 1;\nsetp.lt.u32 p, n, 2000000;\n@p bra WL;\ntrap;\nWD:\n}" :: "r"(bar), "r"(parity) : "memory");
}
__device__ __forceinline__ void mbar_arrive_if(uint32_t bar, bool pred) {
    asm volatile("{\n.reg .pred p;\nsetp.ne.u32 p, %1, 0;\n@p mbarrier.arrive.shared::cta.b64 _, [%0];\n}" :: "r"(bar), "r"((uint32_t)pred) : "memory");
}
__device__ __forceinline__ uint32_t ld_acquire(const unsigned* p) { uint32_t v; asm volatile("ld.acquire.gpu.global.u32 %0, [%1];" : "=r"(v) : "l"(p) : "memory"); return v; }
__device__ __forceinline__ void red_release(unsigned* p) { asm volatile("red.release.gpu.global.add.u32 [%0], 1;" :: "l"(p) : "memory"); }
__device__ __forceinline__ void flag_wait(const unsigned* p, uint32_t target) {
    uint32_t it = 0;
    while ((int)(ld_acquire(p) - target) < 0) { if (++it > 4000000u) __trap(); }
}
__device__ __forceinline__ void fence_async_glob() { asm volatile("fence.proxy.async.global;" ::: "memory"); }
__device__ __forceinline__ void fence_async_smem() { asm volatile("fence.proxy.async.shared::cta;" ::: "memory"); }
__device__ __forceinline__ void bar_sync(int id, int n) { asm volatile("bar.sync %0, %1;" :: "r"(id), "r"(n) : "memory"); }
__device__ __forceinline__ void bulk_load(uint32_t dst, const void* src, uint32_t bytes, uint32_t bar) {
    asm volatile("cp.async.bulk.shared::cluster.global.mbarrier::complete_tx::bytes [%0], [%1], %2, [%3];" :: "r"(dst), "l"(src), "r"(bytes), "r"(bar) : "memory");
}
__device__ __forceinline__ void bulk_store(void* dst, uint32_t src, uint32_t bytes) {
    asm volatile("cp.async.bulk.global.shared::cta.bulk_group [%0], [%1], %2;" :: "l"(dst), "r"(src), "r"(bytes) : "memory");
}
__device__ __forceinline__ void bulk_commit_wait() {
    asm volatile("cp.async.bulk.commit_group;" ::: "memory");
    asm volatile("cp.async.bulk.wait_group 0;" ::: "memory");
}
__device__ __forceinline__ void l2_prefetch(const void* src, uint32_t bytes) { asm volatile("cp.async.bulk.prefetch.L2.global [%0], %1;" :: "l"(src), "r"(bytes) : "memory"); }
__device__ __forceinline__ void tma2d(uint32_t dst, const CUtensorMap* tm, int c0, int c1, uint32_t bar) {
    asm volatile("cp.async.bulk.tensor.2d.shared::cluster.global.mbarrier::complete_tx::bytes [%0], [%1, {%3, %4}], [%2];"
                 :: "r"(dst), "l"(tm), "r"(bar), "r"(c0), "r"(c1) : "memory");
}
__device__ __forceinline__ void tma3d(uint32_t dst, const CUtensorMap* tm, int c0, int c1, int c2, uint32_t bar) {
    asm volatile("cp.async.bulk.tensor.3d.shared::cluster.global.mbarrier::complete_tx::bytes [%0], [%1, {%3, %4, %5}], [%2];"
                 :: "r"(dst), "l"(tm), "r"(bar), "r"(c0), "r"(c1), "r"(c2) : "memory");
}
__device__ __forceinline__ void sts32(uint32_t a, uint32_t v) { asm volatile("st.shared.b32 [%0], %1;" :: "r"(a), "r"(v) : "memory"); }
__device__ __forceinline__ uint32_t lds32(uint32_t a) { uint32_t v; asm volatile("ld.shared.b32 %0, [%1];" : "=r"(v) : "r"(a) : "memory"); return v; }
__device__ __forceinline__ void sts128(uint32_t a, uint32_t x, uint32_t y, uint32_t z, uint32_t w) { asm volatile("st.shared.v4.b32 [%0], {%1, %2, %3, %4};" :: "r"(a), "r"(x), "r"(y), "r"(z), "r"(w) : "memory"); }
__device__ __forceinline__ void stsm4(uint32_t a, uint32_t x, uint32_t y, uint32_t z, uint32_t w) { asm volatile("stmatrix.sync.aligned.m8n8.x4.shared.b16 [%0], {%1, %2, %3, %4};" :: "r"(a), "r"(x), "r"(y), "r"(z), "r"(w) : "memory"); }
__device__ __forceinline__ void ldsm4(uint32_t a, uint32_t& x, uint32_t& y, uint32_t& z, uint32_t& w) { asm volatile("ldmatrix.sync.aligned.m8n8.x4.shared.b16 {%0, %1, %2, %3}, [%4];" : "=r"(x), "=r"(y), "=r"(z), "=r"(w) : "r"(a) : "memory"); }
__device__ __forceinline__ float ex2(float x) { float y; asm("ex2.approx.ftz.f32 %0, %1;" : "=f"(y) : "f"(x)); return y; }
__device__ __forceinline__ float rcp(float x) { float y; asm("rcp.approx.ftz.f32 %0, %1;" : "=f"(y) : "f"(x)); return y; }
__device__ __forceinline__ uint32_t pack_bf16(float lo, float hi) { uint32_t r; asm("cvt.rn.bf16x2.f32 %0, %1, %2;" : "=r"(r) : "f"(hi), "f"(lo)); return r; }
__device__ __forceinline__ float bf_lo(uint32_t v) { return __uint_as_float(v << 16); }
__device__ __forceinline__ float bf_hi(uint32_t v) { return __uint_as_float(v & 0xffff0000u); }
__device__ __forceinline__ float bf_round(float x) { return bf_lo(pack_bf16(x, 0.f)); }
__device__ __forceinline__ uint32_t bf2_sub(uint32_t a, uint32_t b) { uint32_t r; asm("sub.rn.bf16x2 %0, %1, %2;" : "=r"(r) : "r"(a), "r"(b)); return r; }
__device__ __forceinline__ uint32_t bf2_add(uint32_t a, uint32_t b) { uint32_t r; asm("add.rn.bf16x2 %0, %1, %2;" : "=r"(r) : "r"(a), "r"(b)); return r; }
__device__ __forceinline__ uint32_t bf2_mul(uint32_t a, uint32_t b) { uint32_t r; asm("mul.rn.bf16x2 %0, %1, %2;" : "=r"(r) : "r"(a), "r"(b)); return r; }

__device__ __forceinline__ uint32_t bf2_fma(uint32_t a, uint32_t b, uint32_t c) { uint32_t r; asm("fma.rn.bf16x2 %0, %1, %2, %3;" : "=r"(r) : "r"(a), "r"(b), "r"(c)); return r; }
__device__ __forceinline__ void mma16816(float (&d)[4], uint32_t a0, uint32_t a1, uint32_t a2, uint32_t a3, uint32_t b0, uint32_t b1) {
    asm("mma.sync.aligned.m16n8k16.row.col.f32.bf16.bf16.f32 {%0, %1, %2, %3}, {%4, %5, %6, %7}, {%8, %9}, {%0, %1, %2, %3};"
        : "+f"(d[0]), "+f"(d[1]), "+f"(d[2]), "+f"(d[3]) : "r"(a0), "r"(a1), "r"(a2), "r"(a3), "r"(b0), "r"(b1));
}
__device__ __forceinline__ uint4 ldg128(const void* p) { uint4 v; asm volatile("ld.global.nc.L1::no_allocate.v4.u32 {%0, %1, %2, %3}, [%4];" : "=r"(v.x), "=r"(v.y), "=r"(v.z), "=r"(v.w) : "l"(p)); return v; }
__device__ __forceinline__ uint4 ldg128o(const void* p) { uint4 v; asm volatile("ld.global.L1::no_allocate.v4.u32 {%0, %1, %2, %3}, [%4];" : "=r"(v.x), "=r"(v.y), "=r"(v.z), "=r"(v.w) : "l"(p) : "memory"); return v; }
__device__ __forceinline__ uint32_t ldg32(const void* p) { uint32_t v; asm volatile("ld.global.nc.u32 %0, [%1];" : "=r"(v) : "l"(p)); return v; }
__device__ __forceinline__ void cp_async16(uint32_t dst, const void* src) { asm volatile("cp.async.cg.shared.global [%0], [%1], 16;" :: "r"(dst), "l"(src) : "memory"); }
__device__ __forceinline__ uint2 lds64(uint32_t a) { uint2 v; asm volatile("ld.shared.v2.u32 {%0, %1}, [%2];" : "=r"(v.x), "=r"(v.y) : "r"(a) : "memory"); return v; }
__device__ __forceinline__ void sts64(uint32_t a, uint32_t x, uint32_t y) { asm volatile("st.shared.v2.b32 [%0], {%1, %2};" :: "r"(a), "r"(x), "r"(y) : "memory"); }
__device__ __forceinline__ uint32_t mapa(uint32_t a, uint32_t cta) { uint32_t r; asm("mapa.shared::cluster.u32 %0, %1, %2;" : "=r"(r) : "r"(a), "r"(cta)); return r; }
__device__ __forceinline__ void bulk_dsmem(uint32_t dst, uint32_t src, uint32_t bytes, uint32_t bar) {
    asm volatile("cp.async.bulk.shared::cluster.shared::cta.mbarrier::complete_tx::bytes [%0], [%1], %2, [%3];" :: "r"(dst), "r"(src), "r"(bytes), "r"(bar) : "memory");
}
__device__ __forceinline__ void st_async128(uint32_t a, uint32_t x, uint32_t y, uint32_t z, uint32_t w, uint32_t bar) {
    asm volatile("st.async.weak.shared::cluster.mbarrier::complete_tx::bytes.v4.b32 [%0], {%1, %2, %3, %4}, [%5];" :: "r"(a), "r"(x), "r"(y), "r"(z), "r"(w), "r"(bar) : "memory");
}
__device__ __forceinline__ uint4 lds128(uint32_t a) { uint4 v; asm volatile("ld.shared.v4.u32 {%0, %1, %2, %3}, [%4];" : "=r"(v.x), "=r"(v.y), "=r"(v.z), "=r"(v.w) : "r"(a) : "memory"); return v; }

__device__ __forceinline__ float ex2_poly(float x) {
    float u;
    asm("fma.rn.sat.f32 %0, %1, %2, %3;" : "=f"(u) : "f"(x), "f"(1.0f / 254.0f), "f"(126.0f / 254.0f));
    const float MG = 12582912.0f - 126.0f;
    float t = fmaf(u, 254.0f, MG);
    float n2 = MG - t;
    float f = fmaf(u, 254.0f, n2);
    float p;
    p = fmaf(0.009570102207362652f, f, 0.05591785907745361f);
    p = fmaf(p, f, 0.240247443318367f);
    p = fmaf(p, f, 0.6931217908859253f);
    p = fmaf(p, f, 0.9999992847442627f);
    return __uint_as_float(__float_as_uint(p) + (__float_as_uint(t) << 23));
}
template <int C>
__device__ __forceinline__ void chunk(const float (&s)[32], uint32_t (&p)[16]) {
#pragma unroll
    for (int i = 4 * C; i < 4 * C + 4; i++) {
        float a = ((PMASK >> (2 * i)) & 1) ? ex2_poly(s[2 * i]) : ex2(s[2 * i]);
        float b = ((PMASK >> (2 * i + 1)) & 1) ? ex2_poly(s[2 * i + 1]) : ex2(s[2 * i + 1]);
        p[i] = pack_bf16(a, b);
    }
}
#define PV(o, p, C, d) wgmma_rs_n24_t1(o, p[4 * C], p[4 * C + 1], p[4 * C + 2], p[4 * C + 3], (d) + 96 * C, 1)
#define QK0(s, q, d) wgmma_rs_n64_t0(s, q[0], q[1], q[2], q[3], d, 0)
#define QK1(s, q, d) wgmma_rs_n64_t0(s, q[4], q[5], 0u, 0u, (d) + 16, 1)

__device__ __noinline__ void attn_exact_row(const uint32_t* kv, uint32_t qo, int row, int col0) {
    float q[20], o[20];
#pragma unroll
    for (int d = 0; d < 20; d += 2) {
        const int col = col0 + d;
        uint32_t v = lds32(qo + (col >> 3) * 1024 + (row >> 3) * 128 + (row & 7) * 16 + (col & 7) * 2);
        q[d] = bf_lo(v); q[d + 1] = bf_hi(v); o[d] = 0.f; o[d + 1] = 0.f;
    }
    float m = -INFINITY, l = 0.f;
#pragma unroll 1
    for (int key = 0; key < 2048; key++) {
        const uint32_t* p = kv + (key >> 3) * 192 + (key & 7) * 4;
        float s = 0.f;
#pragma unroll
        for (int d = 0; d < 20; d += 2) {
            uint32_t v = __ldcg(p + (d >> 3) * 32 + ((d & 7) >> 1));
            s = fmaf(q[d], bf_lo(v), s); s = fmaf(q[d + 1], bf_hi(v), s);
        }
        const float mn = fmaxf(m, s);
        const float sc = exp2f(m - mn), e = exp2f(s - mn);
        m = mn; l = l * sc + e;
#pragma unroll
        for (int d = 0; d < 20; d += 2) {
            uint32_t v = __ldcg(p + 96 + (d >> 3) * 32 + ((d & 7) >> 1));
            o[d] = fmaf(e, bf_lo(v), o[d] * sc); o[d + 1] = fmaf(e, bf_hi(v), o[d + 1] * sc);
        }
    }
    const float il = 1.0f / l;
#pragma unroll
    for (int d = 0; d < 20; d += 2) {
        const int col = col0 + d;
        sts32(qo + (col >> 3) * 1024 + (row >> 3) * 128 + (row & 7) * 16 + (col & 7) * 2, pack_bf16(o[d] * il, o[d + 1] * il));
    }
}

template <int NV>
__device__ __forceinline__ void ln_rows(const uint4 (&v)[NV], int lane, uint32_t xa) {
    float a0[4] = {0.f, 0.f, 0.f, 0.f}, a1[4] = {0.f, 0.f, 0.f, 0.f};
#pragma unroll
    for (int t = 0; t < NV; t++) {
        mma16816(a0, v[t].x, 0x3F803F80u, v[t].y, 0x3F803F80u, v[t].x, v[t].y);
        mma16816(a1, v[t].z, 0x3F803F80u, v[t].w, 0x3F803F80u, v[t].z, v[t].w);
    }
    const float cs = (a0[2] + a0[3]) + (a1[2] + a1[3]);
    const float dg = (lane & 4) ? a0[1] + a1[1] : a0[0] + a1[0];
    float s, sq;
    if (NV == 5) {
        const int h = lane >> 4;
        s = __shfl_sync(~0u, cs, h * 2) + __shfl_sync(~0u, cs, h * 2 + 1);
        sq = (__shfl_sync(~0u, dg, h * 18) + __shfl_sync(~0u, dg, h * 18 + 4)) + (__shfl_sync(~0u, dg, h * 18 + 9) + __shfl_sync(~0u, dg, h * 18 + 13));
    } else {
        const int h = lane >> 3;
        s = __shfl_sync(~0u, cs, h);
        sq = __shfl_sync(~0u, dg, h * 9) + __shfl_sync(~0u, dg, h * 9 + 4);
    }
    const float mean = s * (1.0f / 640.0f);
    float var = fmaf(sq, 1.0f / 640.0f, -mean * mean);
    if (__any_sync(~0u, !(mean * mean <= 16.0f * var))) {
        float s0 = 0.f, s1 = 0.f;
#pragma unroll
        for (int t = 0; t < NV; t++) {
            float a;
            a = bf_lo(v[t].x) - mean; s0 = fmaf(a, a, s0); a = bf_hi(v[t].x) - mean; s1 = fmaf(a, a, s1);
            a = bf_lo(v[t].y) - mean; s0 = fmaf(a, a, s0); a = bf_hi(v[t].y) - mean; s1 = fmaf(a, a, s1);
            a = bf_lo(v[t].z) - mean; s0 = fmaf(a, a, s0); a = bf_hi(v[t].z) - mean; s1 = fmaf(a, a, s1);
            a = bf_lo(v[t].w) - mean; s0 = fmaf(a, a, s0); a = bf_hi(v[t].w) - mean; s1 = fmaf(a, a, s1);
        }
        s0 += s1;
#pragma unroll
        for (int o = 1; o < 80 / NV; o <<= 1) s0 += __shfl_xor_sync(~0u, s0, o);
        var = s0 * (1.0f / 640.0f);
    }
    float sd;
    asm("sqrt.approx.f32 %0, %1;" : "=f"(sd) : "f"(bf_round(bf_round(var) + 1e-5f)));
    const float rinv = rcp(bf_round(sd));
    const float rh = bf_round(rinv);
    const uint32_t m2 = pack_bf16(mean, mean), rh2 = pack_bf16(rh, rh), rl2 = pack_bf16(rinv - rh, rinv - rh);
#pragma unroll
    for (int t = 0; t < NV; t++) {
        const uint32_t d0 = bf2_sub(v[t].x, m2), d1 = bf2_sub(v[t].y, m2), d2 = bf2_sub(v[t].z, m2), d3 = bf2_sub(v[t].w, m2);
        sts128(xa + t * (81920 / NV), bf2_fma(d0, rh2, bf2_mul(d0, rl2)), bf2_fma(d1, rh2, bf2_mul(d1, rl2)),
               bf2_fma(d2, rh2, bf2_mul(d2, rl2)), bf2_fma(d3, rh2, bf2_mul(d3, rl2)));
    }
}

struct Params {
    const __nv_bfloat16 *x, *wk, *wv;
    Scratch* s;
    const __nv_bfloat16 *wq, *wo, *wg, *wu, *wd;
    __nv_bfloat16* out;
};

__global__ void __launch_bounds__(512, 1)
fused_kernel(const Params P, const __grid_constant__ CUtensorMap tm_wq, const __grid_constant__ CUtensorMap tm_wq32, const __grid_constant__ CUtensorMap tm_wg, const __grid_constant__ CUtensorMap tm_wu,
             const __grid_constant__ CUtensorMap tm_wd, const __grid_constant__ CUtensorMap tm_wo) {
    const uint32_t t_launch = (uint32_t)clock();
    extern __shared__ __align__(1024) char smem_raw[];
    const uint32_t sb = smem_u32(smem_raw);
    const uint32_t bars = sb + BAR_OFF;
    const int tid = threadIdx.x, lane = tid & 31;
    const int warp_id = __shfl_sync(~0u, tid >> 5, 0);
    const int wg = warp_id >> 2, warp = warp_id & 3;
    const int r = lane >> 2, c = lane & 3;
    const int bid = blockIdx.x;
    const int rb = bid >> 2, cb = bid & 3, rank = bid & 1;
    constexpr float QSCALE = 0.22360679774997896f * 1.4426950408889634f;

    const int lrow = ((tid >> 3) ^ (rank << 5) ^ 32) & 63;
    const uint4* xr = (const uint4*)(P.x + (size_t)(rb * 64 + lrow) * 640) + (lane & 7);
    const uint32_t xa = sb + XN_OFF + lrow * 128 + (((lane ^ lrow) & 7) << 4);
    if (wg >= 2) {
        uint4 v[10];
#pragma unroll
        for (int t = 0; t < 10; t++) v[t] = ldg128(xr + 8 * t);
        PROF(42);
        ln_rows<10>(v, lane, xa);
        PROF(22 + wg);
        bar_sync(4, 512);
        PROF(27);
    }

    if (wg < 2) {
        if (tid == 0) {
            mbar_init(bars + B_WKV * 8, 1); mbar_init(bars + B_SLAB * 8, 1); mbar_init(bars + B_SLAB2 * 8, 1);
            asm volatile("fence.mbarrier_init.release.cluster;" ::: "memory");
            mbar_expect_tx(bars + B_WKV * 8, 25600);
            bulk_load(sb + WRAW_OFF, cb < 2 ? P.wk : P.wv, 25600, bars + B_WKV * 8);
            mbar_expect_tx(bars + B_SLAB * 8, 92160);
            asm volatile("prefetch.tensormap [%0];" :: "l"(&tm_wq32) : "memory");
        }
        if (tid == 32) {
            mbar_init(bars + B_SLABFREE * 8, 8);
            for (int i = 0; i < 4; i++) { mbar_init(bars + (B_KVFULL + i) * 8, 1); mbar_init(bars + (B_KVEMPTY + i) * 8, 8); mbar_init(bars + (B_WO + i) * 8, 1); }
            for (int i = 0; i < 3; i++) { mbar_init(bars + (B_RING + i) * 8, 1); mbar_init(bars + (B_REMPTY + i) * 8, 4); }
            mbar_init(bars + B_KVALL * 8, 1);
            mbar_init(bars + B_Q2 * 8, 4); mbar_init(bars + B_OREADY * 8, 8); mbar_init(bars + B_QOFREE * 8, 1);
            mbar_init(bars + B_OBLOB * 8, 1); mbar_init(bars + B_XT * 8, 1);
            mbar_init(bars + B_HFULL * 8, 4); mbar_init(bars + B_HFREE * 8, 1); mbar_init(bars + B_WODONE * 8, 4);
            l2_prefetch((const char*)P.wq + bid * 6400, 6400);
        }
        bar_sync(6, 256);
        uint4 v[10];
#pragma unroll
        for (int t = 0; t < 10; t++) v[t] = ldg128o(xr + 8 * t);
        if (tid == 224) {
            while ((uint32_t)clock() - t_launch < SLAB_DELAY) {}
            for (int i = 0; i < 3; i++) tma3d(sb + RING_OFF + i * 30720, &tm_wq32, 0, i * 160, cb * 5, bars + B_SLAB * 8);
            PROFW(32);
        }
        __syncwarp();
        mbar_wait(bars + B_WKV * 8, 0);
        PROF(38);
        {
            const uint32_t src = sb + WRAW_OFF + tid * 40, dst = sb + WKV_OFF + (tid >> 3) * 384 + (tid & 7) * 16;
#pragma unroll
            for (int i = 0; i < 3; i++) {
                if (i < 2 || wg == 0) {
                    const uint32_t sa = src + i * 10240, da = dst + i * 12288;
                    const uint2 w0 = lds64(sa), w1 = lds64(sa + 8), w2 = lds64(sa + 16), w3 = lds64(sa + 24), w4 = lds64(sa + 32);
                    sts128(da, w0.x, w0.y, w1.x, w1.y);
                    sts128(da + 128, w2.x, w2.y, w3.x, w3.y);
                    sts64(da + 256, w4.x, w4.y);
                }
            }
        }
        asm volatile("bar.arrive 4, 512;" ::: "memory");
        PROF(37);
        ln_rows<10>(v, lane, xa);
        PROF(39 + wg);
        if (wg == 1) asm volatile("bar.arrive 2, 384;" ::: "memory");
        asm volatile("setmaxnreg.inc.sync.aligned.u32 152;");
        uint32_t qa[6], qb[6];
        {
            float d[24];
            mbar_wait(bars + B_SLAB * 8, 0);
            PROF(33 + wg);
            bar_sync(2 + wg, wg ? 256 : 384);
            fence_async_smem();
            const uint64_t dA = mkdesc(sb + XN_OFF, 16, 1024, 1);
            const uint64_t dB = mkdesc(sb + RING_OFF + wg * 10240, 10240, 512, 2);
            wg_fence();
#pragma unroll
            for (int k = 0; k < 30; k++) wgmma_ss_n48(d, dA + (k >> 2) * 512 + (k & 3) * 2, dB + (k / 10) * 1920 + (k % 10) * 64, k != 0);
            wg_commit();
            if (wg == 0) asm volatile("bar.arrive 3, 256;" ::: "memory");
            mbar_wait(bars + B_SLAB2 * 8, 0);
            wg_fence();
#pragma unroll
            for (int k = 30; k < 40; k++) wgmma_ss_n48(d, dA + (k >> 2) * 512 + (k & 3) * 2, dB + (k / 10) * 1920 + (k % 10) * 64, 1);
            wg_commit();
            wg_wait<0>();
#pragma unroll
            for (int i = 0; i < 24; i++) asm volatile("" : "+f"(d[i]) :: "memory");
            if (lane == 0) mbar_arrive(bars + B_SLABFREE * 8);
            uint32_t p0[5], p1[5];
#pragma unroll
            for (int i = 0; i < 5; i++) {
                p0[i] = pack_bf16((wg ? d[4 * i + 4] : d[4 * i]) * QSCALE, (wg ? d[4 * i + 5] : d[4 * i + 1]) * QSCALE);
                p1[i] = pack_bf16((wg ? d[4 * i + 6] : d[4 * i + 2]) * QSCALE, (wg ? d[4 * i + 7] : d[4 * i + 3]) * QSCALE);
            }
            qa[0] = p0[0]; qa[1] = p1[0]; qa[2] = p0[1]; qa[3] = p1[1];
            qa[4] = c < 2 ? p0[2] : 0u; qa[5] = c < 2 ? p1[2] : 0u;
            qb[0] = __shfl_xor_sync(~0u, c >= 2 ? p0[2] : p0[3], 2); qb[1] = __shfl_xor_sync(~0u, c >= 2 ? p1[2] : p1[3], 2);
            qb[2] = __shfl_xor_sync(~0u, c >= 2 ? p0[3] : p0[4], 2); qb[3] = __shfl_xor_sync(~0u, c >= 2 ? p1[3] : p1[4], 2);
            qb[4] = __shfl_xor_sync(~0u, c >= 2 ? p0[4] : 0u, 2); qb[5] = __shfl_xor_sync(~0u, c >= 2 ? p1[4] : 0u, 2);
        }
        PROF(1 + wg * 8);

        const uint64_t dK0 = mkdesc(sb + KVR_OFF, 128, 768, 0);
        const uint64_t dV0 = mkdesc(sb + KVR_OFF + 384, 768, 128, 0);
        const uint32_t qo_a = sb + QO_OFF + wg * 5120 + warp * 256 + r * 16 + c * 4;
        const uint32_t qo_b = sb + QO_OFF + wg * 5120 + warp * 256 + r * 16 + (c < 2 ? 2048 + 8 + c * 4 : 3072 + (c - 2) * 4);
#pragma unroll 1
        for (int pass = 0; pass < 2; pass++) {
            float sa[32], sbb[32], oa[12], ob[12];
            uint32_t pa[16], pb[16];
#pragma unroll
            for (int i = 0; i < 12; i++) { oa[i] = 0.f; ob[i] = 0.f; }
            mbar_wait(bars + B_KVFULL * 8, 0);
            PROF(6 + pass + wg * 8);
            wg_fence();
            QK0(sa, qa, dK0); QK1(sa, qa, dK0); QK0(sbb, qb, dK0); QK1(sbb, qb, dK0);
            wg_commit(); wg_wait<0>();
#pragma unroll
            for (int i = 0; i < 32; i++) asm volatile("" : "+f"(sa[i]), "+f"(sbb[i]) :: "memory");
            {
                float m0 = -INFINITY, m1 = -INFINITY, m2 = -INFINITY, m3 = -INFINITY;
#pragma unroll
                for (int j = 0; j < 8; j++) {
                    m0 = fmaxf(m0, fmaxf(sa[4 * j], sa[4 * j + 1])); m1 = fmaxf(m1, fmaxf(sa[4 * j + 2], sa[4 * j + 3]));
                    m2 = fmaxf(m2, fmaxf(sbb[4 * j], sbb[4 * j + 1])); m3 = fmaxf(m3, fmaxf(sbb[4 * j + 2], sbb[4 * j + 3]));
                }
#pragma unroll
                for (int o = 1; o < 4; o <<= 1) {
                    m0 = fmaxf(m0, __shfl_xor_sync(~0u, m0, o)); m1 = fmaxf(m1, __shfl_xor_sync(~0u, m1, o));
                    m2 = fmaxf(m2, __shfl_xor_sync(~0u, m2, o)); m3 = fmaxf(m3, __shfl_xor_sync(~0u, m3, o));
                }
                if (c == 2) {
                    qa[4] = pack_bf16(-(m0 + 80.f), 0.f); qa[5] = pack_bf16(-(m1 + 80.f), 0.f);
                    qb[4] = pack_bf16(-(m2 + 80.f), 0.f); qb[5] = pack_bf16(-(m3 + 80.f), 0.f);
                }
            }
            wg_fence();
            QK0(sa, qa, dK0); QK1(sa, qa, dK0);
            wg_commit(); wg_wait<0>();
            pb[12] = pb[13] = pb[14] = pb[15] = 0u;
            uint64_t dVp = dV0;
#pragma unroll 1
            for (int g = pass * 32; g < pass * 32 + 32; g++) {
                const uint64_t dK = dK0 + (g & 3) * 384, dV = dV0 + (g & 3) * 384;
                const int gn = g < 63 ? g + 1 : g;
                const uint64_t dKn = dK0 + (gn & 3) * 384;
                wg_fence(); PV(ob, pb, 3, dVp); wg_commit();
                chunk<0>(sa, pa);
                wg_fence(); QK0(sbb, qb, dK); PV(oa, pa, 0, dV); wg_commit();
                chunk<1>(sa, pa);
                wg_fence(); QK1(sbb, qb, dK); PV(oa, pa, 1, dV); wg_commit();
                chunk<2>(sa, pa);
                wg_fence(); PV(oa, pa, 2, dV); wg_commit();
                const bool nxt = mbar_try(bars + (B_KVFULL + (gn & 3)) * 8, (gn >> 2) & 1);
                chunk<3>(sa, pa);
                wg_wait<1>();
                mbar_arrive_if(bars + (B_KVEMPTY + ((g - 1) & 3)) * 8, lane == 0 && g > 0);
                wg_fence(); PV(oa, pa, 3, dV); wg_commit();
                chunk<0>(sbb, pb);
                if (!nxt) mbar_wait(bars + (B_KVFULL + (gn & 3)) * 8, (gn >> 2) & 1);
                wg_fence(); QK0(sa, qa, dKn); PV(ob, pb, 0, dV); wg_commit();
                chunk<1>(sbb, pb);
                wg_fence(); QK1(sa, qa, dKn); PV(ob, pb, 1, dV); wg_commit();
                chunk<2>(sbb, pb);
                wg_fence(); PV(ob, pb, 2, dV); wg_commit();
                chunk<3>(sbb, pb);
                wg_wait<1>();
                dVp = dV;
            }
            wg_fence(); PV(ob, pb, 3, dVp); wg_commit();
            wg_wait<0>();
#pragma unroll
            for (int i = 0; i < 12; i++) asm volatile("" : "+f"(oa[i]), "+f"(ob[i]) :: "memory");
            PROF(2 + pass * 2 + wg * 8);
            uint32_t na[6], nb[6];
            if (pass == 0) {
                mbar_wait(bars + B_Q2 * 8, 0);
                na[0] = lds32(qo_a); na[1] = lds32(qo_a + 128); na[2] = lds32(qo_a + 1024); na[3] = lds32(qo_a + 1152);
                na[4] = c < 2 ? lds32(qo_a + 2048) : 0u; na[5] = c < 2 ? lds32(qo_a + 2176) : 0u;
                nb[0] = lds32(qo_b); nb[1] = lds32(qo_b + 128); nb[2] = lds32(qo_b + 1024); nb[3] = lds32(qo_b + 1152);
                nb[4] = c < 2 ? lds32(qo_b + 2048) : 0u; nb[5] = c < 2 ? lds32(qo_b + 2176) : 0u;
                __syncwarp();
            } else {
                mbar_wait(bars + B_QOFREE * 8, 0);
#pragma unroll
                for (int i = 0; i < 6; i++) { na[i] = 0u; nb[i] = 0u; }
            }
            const int src = (lane & ~3) | 2;
            const float l0 = __shfl_sync(~0u, oa[8], src), l1 = __shfl_sync(~0u, oa[10], src);
            const float l2 = __shfl_sync(~0u, ob[8], src), l3 = __shfl_sync(~0u, ob[10], src);
            const float LO = 8.0779e-28f  , HI = 1.0e37f;
            bool ok = (l0 >= LO) && (l0 <= HI) && (l1 >= LO) && (l1 <= HI) && (l2 >= LO) && (l2 <= HI) && (l3 >= LO) && (l3 <= HI);
            float amax = 0.f;
#pragma unroll
            for (int i = 0; i < 12; i++) amax = amax + fabsf(oa[i]) * 0.03125f + fabsf(ob[i]) * 0.03125f;
            ok = ok && (amax <= 3.0e38f);
            if (__all_sync(~0u, ok)) {
                const float i0 = rcp(l0), i1 = rcp(l1), i2 = rcp(l2), i3 = rcp(l3);
                sts32(qo_a, pack_bf16(oa[0] * i0, oa[1] * i0)); sts32(qo_a + 128, pack_bf16(oa[2] * i1, oa[3] * i1));
                sts32(qo_a + 1024, pack_bf16(oa[4] * i0, oa[5] * i0)); sts32(qo_a + 1152, pack_bf16(oa[6] * i1, oa[7] * i1));
                sts32(qo_b, pack_bf16(ob[0] * i2, ob[1] * i2)); sts32(qo_b + 128, pack_bf16(ob[2] * i3, ob[3] * i3));
                sts32(qo_b + 1024, pack_bf16(ob[4] * i2, ob[5] * i2)); sts32(qo_b + 1152, pack_bf16(ob[6] * i3, ob[7] * i3));
                if (c < 2) {
                    sts32(qo_a + 2048, pack_bf16(oa[8] * i0, oa[9] * i0)); sts32(qo_a + 2176, pack_bf16(oa[10] * i1, oa[11] * i1));
                    sts32(qo_b + 2048, pack_bf16(ob[8] * i2, ob[9] * i2)); sts32(qo_b + 2176, pack_bf16(ob[10] * i3, ob[11] * i3));
                }
            } else {
                sts32(qo_a, qa[0]); sts32(qo_a + 128, qa[1]); sts32(qo_a + 1024, qa[2]); sts32(qo_a + 1152, qa[3]);
                sts32(qo_b, qb[0]); sts32(qo_b + 128, qb[1]); sts32(qo_b + 1024, qb[2]); sts32(qo_b + 1152, qb[3]);
                if (c < 2) { sts32(qo_a + 2048, qa[4]); sts32(qo_a + 2176, qa[5]); sts32(qo_b + 2048, qb[4]); sts32(qo_b + 2176, qb[5]); }
                __syncwarp();
                mbar_wait(bars + B_KVALL * 8, 0);
                attn_exact_row((const uint32_t*)g_kv, sb + QO_OFF, warp * 16 + (lane & 15), wg * 40 + (lane >> 4) * 20);
            }
            fence_async_smem();
            __syncwarp();
            if (lane == 0) mbar_arrive(bars + B_OREADY * 8);
#pragma unroll
            for (int i = 0; i < 6; i++) { qa[i] = na[i]; qb[i] = nb[i]; }
            PROF(3 + pass * 2 + wg * 8);
        }
    } else if (wg == 2) {
        const uint64_t dXN = mkdesc(sb + XN_OFF, 16, 1024, 1);
        {
            float d[12];
            const uint64_t dB = mkdesc(sb + WKV_OFF, 384, 128, 0);
            fence_async_smem();
            PROF(43);
            wg_fence();
#pragma unroll
            for (int k = 0; k < 40; k++) wgmma_ss_n24(d, dXN + (k >> 2) * 512 + (k & 3) * 2, dB + k * 48, k != 0);
            wg_commit();
            asm volatile("bar.arrive 2, 384;" ::: "memory");
            PROF(44);
            wg_wait<0>();
            PROF(45);
#pragma unroll
            for (int i = 0; i < 12; i++) asm volatile("" : "+f"(d[i]) :: "memory");
            if ((warp >> 1) == rank) {
                uint32_t* kvb = (uint32_t*)((char*)g_kv + rb * 6144 + warp * 1536 + (cb >> 1) * 384) + lane;
                const uint32_t cst = c == 2 ? 0x00003F80u : 0u;
                kvb[0] = pack_bf16(d[0], d[1]); kvb[192] = pack_bf16(d[2], d[3]);
                kvb[32] = pack_bf16(d[4], d[5]); kvb[224] = pack_bf16(d[6], d[7]);
                kvb[64] = c < 2 ? pack_bf16(d[8], d[9]) : cst; kvb[256] = c < 2 ? pack_bf16(d[10], d[11]) : cst;
                PROFW(16);
                asm volatile("bar.arrive 5, 128;" ::: "memory");
                fence_async_glob();
                __syncwarp();
                if (lane == 0) red_release(&g_flag_kv[rb]);
                PROFW(41);
            } else {
                bar_sync(5, 128);
                if ((warp & 1) == 0 && lane == 0) {
                    mbar_expect_tx(bars + B_SLAB2 * 8, 30720);
                    tma3d(sb + RING_OFF + 92160, &tm_wq32, 0, 480, cb * 5, bars + B_SLAB2 * 8);
                }
                __syncwarp();
            }
        }
        PROF(17);
        asm volatile("setmaxnreg.inc.sync.aligned.u32 168;");
        {
            float d[40];
#pragma unroll 1
            for (int s = 0; s < 5; s++) {
                const int sl = s % 3;
                mbar_wait(bars + (B_RING + sl) * 8, (s / 3) & 1);
                if (s == 0) fence_async_smem();
                const uint64_t dB = mkdesc(sb + RING_OFF + sl * 32768, 8192, 1024, 1);
#pragma unroll
                for (int k = 0; k < 8; k += 2) {
                    wg_fence();
                    wgmma_ss_n80(d, dXN + (2 * s + (k >> 2)) * 512 + (k & 3) * 2, dB + (k >> 2) * 1024 + (k & 3) * 128, (s | k) != 0);
                    wgmma_ss_n80(d, dXN + (2 * s + (k >> 2)) * 512 + (k & 3) * 2 + 2, dB + (k >> 2) * 1024 + (k & 3) * 128 + 128, 1);
                    wg_commit(); wg_wait<0>();
                }
                mbar_arrive_if(bars + (B_REMPTY + sl) * 8, lane == 0);
            }
#pragma unroll
            for (int i = 0; i < 40; i++) asm volatile("" : "+f"(d[i]) :: "memory");
            const uint32_t qa_ = sb + QO_OFF + warp * 256 + r * 16 + c * 4;
#pragma unroll
            for (int j = 0; j < 10; j++) {
                sts32(qa_ + j * 1024, pack_bf16(d[4 * j] * QSCALE, d[4 * j + 1] * QSCALE));
                sts32(qa_ + j * 1024 + 128, pack_bf16(d[4 * j + 2] * QSCALE, d[4 * j + 3] * QSCALE));
            }
            __syncwarp();
            if (lane == 0) mbar_arrive(bars + B_Q2 * 8);
        }
        PROF(18);
        int sl = 2, ph = 1;
#pragma unroll 1
        for (int jj = 0; jj < 3; jj++) {
            float d[64], e[64];
#pragma unroll 1
            for (int kc = 0; kc < 10; kc++) {
                mbar_wait(bars + (B_RING + sl) * 8, ph);
                const uint64_t dB = mkdesc(sb + RING_OFF + sl * 32768, 8192, 1024, 1);
#pragma unroll
                for (int k = 0; k < 4; k++) {
                    wg_fence();
                    wgmma_ss_n128(d, dXN + kc * 512 + k * 2, dB + k * 128, (kc | k) != 0);
                    wgmma_ss_n128(e, dXN + kc * 512 + k * 2, dB + 1024 + k * 128, (kc | k) != 0);
                    wg_commit(); wg_wait<0>();
                }
                mbar_arrive_if(bars + (B_REMPTY + sl) * 8, lane == 0);
                if (++sl == 3) { sl = 0; ph ^= 1; }
            }
#pragma unroll
            for (int i = 0; i < 64; i++) asm volatile("" : "+f"(d[i]), "+f"(e[i]) :: "memory");
            mbar_wait(bars + B_HFREE * 8, (jj & 1) ^ 1);
            const int mrow = warp * 16 + ((lane >> 3) & 1) * 8 + (lane & 7);
            const uint32_t ha = sb + HST_OFF + mrow * 128;
#pragma unroll
            for (int j = 0; j < 16; j += 2) {
                uint32_t h[4];
#pragma unroll
                for (int i = 0; i < 4; i++)
                    h[i] = bf2_mul(pack_bf16(d[4 * j + 2 * i], d[4 * j + 2 * i + 1]), pack_bf16(e[4 * j + 2 * i], e[4 * j + 2 * i + 1]));
                const int blk = (j & 7) + (lane >> 4);
                stsm4(ha + (j >> 3) * 8192 + ((blk ^ (mrow & 7)) << 4), h[0], h[1], h[2], h[3]);
            }
            fence_async_smem();
            __syncwarp();
            if (lane == 0) mbar_arrive(bars + B_HFULL * 8);
            PROF(19 + jj);
        }
        uint32_t gs[40];
        {
            float d[80];
#pragma unroll 1
            for (int kc = 0; kc < 24; kc++) {
                mbar_wait(bars + (B_RING + sl) * 8, ph);
                const uint64_t dA = mkdesc(sb + RING_OFF + sl * 32768, 16, 1024, 1);
                const uint64_t dB = mkdesc(sb + RING_OFF + sl * 32768 + 8192, 8192, 1024, 1);
#pragma unroll
                for (int k = 0; k < 4; k++) {
                    wg_fence();
                    wgmma_ss_n160(d, dA + k * 2, dB + k * 128, (kc | k) != 0);
                    wg_commit(); wg_wait<0>();
                }
                mbar_arrive_if(bars + (B_REMPTY + sl) * 8, lane == 0);
                if (++sl == 3) { sl = 0; ph ^= 1; }
            }
#pragma unroll
            for (int i = 0; i < 80; i++) asm volatile("" : "+f"(d[i]) :: "memory");
#pragma unroll
            for (int i = 0; i < 40; i++) {
                const uint32_t y2 = pack_bf16(d[2 * i], d[2 * i + 1]);
                const float y0 = bf_lo(y2), y1 = bf_hi(y2);
                gs[i] = pack_bf16(y0 * rcp(1.0f + ex2(y0 * -1.4426950408889634f)), y1 * rcp(1.0f + ex2(y1 * -1.4426950408889634f)));
            }
        }
        PROF(22);
        {
            float d[80];
            mbar_wait(bars + B_OBLOB * 8, 0);
#pragma unroll 1
            for (int i = 0; i < 4; i++) {
                mbar_wait(bars + (B_WO + i) * 8, 0);
                const uint64_t dA = mkdesc(sb + XN_OFF + i * 10240, 1024, 128, 0);
                const uint64_t dB = mkdesc(sb + RING_OFF + i * 25600, 5120, 512, 2);
#pragma unroll
                for (int k = 0; k < 5; k++) {
                    wg_fence();
                    wgmma_ss_n160(d, dA + k * 128, dB + k * 64, (i | k) != 0);
                    wg_commit(); wg_wait<0>();
                }
            }
            mbar_arrive_if(bars + B_WODONE * 8, lane == 0);
            PROF(23);
#pragma unroll
            for (int i = 0; i < 4; i++) mbar_wait(bars + (B_WO + i) * 8, 1);
            mbar_wait(bars + B_XT * 8, 0);
            const uint64_t dB = mkdesc(sb + RING_OFF, 5120, 512, 2);
            mbar_wait(bars + B_OREADY * 8, 1);
            PROF(28);
            {
                const uint64_t dA = mkdesc(sb + QO_OFF, 1024, 128, 0);
                wg_fence();
#pragma unroll
                for (int k = 0; k < 5; k++) wgmma_ss_n160(d, dA + k * 128, dB + k * 64, 1);
                wg_commit();
            }
            mbar_wait(bars + B_OBLOB * 8, 1);
            PROF(29);
            {
                const uint64_t dA = mkdesc(sb + XN_OFF, 1024, 128, 0);
                wg_fence();
#pragma unroll
                for (int k = 5; k < 20; k++) wgmma_ss_n160(d, dA + (k / 5) * 640 + (k % 5) * 128, dB + (k / 5) * 1600 + (k % 5) * 64, 1);
                wg_commit();
            }
            wg_wait<0>();
#pragma unroll
            for (int i = 0; i < 80; i++) asm volatile("" : "+f"(d[i]) :: "memory");
            PROF(30);
            const int mrow = warp * 16 + ((lane >> 3) & 1) * 8 + (lane & 7);
            const uint32_t xa = sb + XT_OFF + mrow * 336 + (lane >> 4) * 16;
#pragma unroll
            for (int j = 0; j < 20; j += 2) {
                uint32_t x[4];
                ldsm4(xa + j * 16, x[0], x[1], x[2], x[3]);
#pragma unroll
                for (int i = 0; i < 4; i++)
                    x[i] = bf2_add(x[i], bf2_mul(pack_bf16(d[4 * j + 2 * i], d[4 * j + 2 * i + 1]), gs[2 * j + i]));
                stsm4(xa + j * 16, x[0], x[1], x[2], x[3]);
            }
            __syncwarp();
#pragma unroll
            for (int i = 0; i < 10; i++) {
                const int idx = lane + 32 * i, row = warp * 16 + idx / 20, ch = idx % 20;
                const uint4 o4 = lds128(sb + XT_OFF + row * 336 + ch * 16);
                *(uint4*)((char*)P.out + (size_t)(rb * 64 + row) * 1280 + cb * 320 + ch * 16) = o4;
            }
            PROF(31);
        }
    } else {
        asm volatile("setmaxnreg.dec.sync.aligned.u32 40;");
        if (warp == 3) {
            if (lane == 0) {
                mbar_wait(bars + B_KVALL * 8, 0);
                l2_prefetch((const char*)P.wg + bid * 15360, 15360);
                l2_prefetch((const char*)P.wu + bid * 15360, 15360);
                l2_prefetch((const char*)P.wd + bid * 15360, 15360);
                l2_prefetch((const char*)P.wo + bid * 6400, 6400);
            }
            return;
        }
        uint32_t epoch;
        asm volatile("ld.relaxed.gpu.global.u32 %0, [%1];" : "=r"(epoch) : "l"(&g_epoch[bid]));
        epoch += 1u;
        if (warp == 0) {
            const int tile = (rb + lane) & 31;
            bool seen = false, issued = lane >= 4;
            for (uint32_t it = 0;; it++) {
                if (!seen) seen = (int)(ld_acquire(&g_flag_kv[tile]) - epoch * 8u) >= 0;
                const uint32_t m = __ballot_sync(~0u, seen);
                if (!issued && seen && (m & 1u)) {
                    issued = true;
                    PROFW(35);
                    fence_async_glob();
                    mbar_expect_tx(bars + (B_KVFULL + lane) * 8, 6144);
                    bulk_load(sb + KVR_OFF + lane * 6144, (const char*)g_kv + tile * 6144, 6144, bars + (B_KVFULL + lane) * 8);
                }
                if (m == ~0u) break;
                if (it > 4000000u) __trap();
            }
            PROFW(36);
            fence_async_glob();
            __syncwarp();
            if (lane == 0) {
                mbar_arrive(bars + B_KVALL * 8);
                for (int g = 4; g < 64; g++) {
                    mbar_wait(bars + (B_KVEMPTY + (g & 3)) * 8, ((g >> 2) - 1) & 1);
                    mbar_expect_tx(bars + (B_KVFULL + (g & 3)) * 8, 6144);
                    bulk_load(sb + KVR_OFF + (g & 3) * 6144, (const char*)g_kv + ((rb + g) & 31) * 6144, 6144, bars + (B_KVFULL + (g & 3)) * 8);
                }
            }
        } else if (warp == 1) {
            if (lane == 0) {
                mbar_wait(bars + B_SLABFREE * 8, 0);
                int sl = 0, ph = 1;
                for (int s = 0; s < 59; s++) {
                    mbar_wait(bars + (B_REMPTY + sl) * 8, ph);
                    const uint32_t slot = sb + RING_OFF + sl * 32768, bar = bars + (B_RING + sl) * 8;
                    if (s < 5) {
                        mbar_expect_tx(bar, 32768);
                        for (int i = 0; i < 4; i++) tma2d(slot + i * 8192, &tm_wq, cb * 160 + 80 + 64 * (i & 1), (2 * s + (i >> 1)) * 64, bar);
                    } else if (s < 35) {
                        const int jj = (s - 5) / 10, kc = (s - 5) % 10;
                        mbar_expect_tx(bar, 32768);
                        tma3d(slot, &tm_wg, 0, kc * 64, cb * 6 + jj * 2, bar);
                        tma3d(slot + 16384, &tm_wu, 0, kc * 64, cb * 6 + jj * 2, bar);
                    } else {
                        const int kc = s - 35;
                        mbar_expect_tx(bar, 32768);
                        for (int i = 0; i < 3; i++) tma2d(slot + 8192 + i * 8192, &tm_wd, cb * 160 + 64 * i, kc * 64, bar);
                        if (s == 35) { flag_wait(&g_flag_h[rb], epoch * 12u); fence_async_glob(); }
                        bulk_load(slot, (const char*)g_h + (size_t)(rb * 24 + kc) * 8192, 8192, bar);
                    }
                    if (++sl == 3) { sl = 0; ph ^= 1; }
                }
                for (int s = 0; s < 3; s++) {
                    mbar_wait(bars + (B_REMPTY + sl) * 8, ph);
                    if (++sl == 3) { sl = 0; ph ^= 1; }
                }
                for (int pass = 0; pass < 2; pass++) {
                    if (pass) mbar_wait(bars + B_WODONE * 8, 0);
                    for (int i = 0; i < 4; i++) {
                        mbar_expect_tx(bars + (B_WO + i) * 8, 25600);
                        tma3d(sb + RING_OFF + i * 25600, &tm_wo, 0, ((cb + i) & 3) * 160 + pass * 80, cb * 5, bars + (B_WO + i) * 8);
                    }
                }
            }
        } else {
            if (lane == 0) {
                for (int jj = 0; jj < 3; jj++) {
                    mbar_wait(bars + B_HFULL * 8, jj & 1);
                    bulk_store((char*)g_h + (size_t)(rb * 24 + cb * 6 + jj * 2) * 8192, sb + HST_OFF, 16384);
                    bulk_commit_wait();
                    fence_async_glob();
                    red_release(&g_flag_h[rb]);
                    mbar_arrive(bars + B_HFREE * 8);
                }
                for (int pass = 0; pass < 2; pass++) {
                    mbar_wait(bars + B_OREADY * 8, pass);
                    bulk_store((char*)g_o + (size_t)(rb * 8 + pass * 4 + cb) * 10240, sb + QO_OFF, 10240);
                    bulk_commit_wait();
                    fence_async_glob();
                    red_release(&g_flag_o[rb * 2 + pass]);
                    if (pass == 0) mbar_arrive(bars + B_QOFREE * 8);
                    else mbar_wait(bars + B_WODONE * 8, 0);
                    mbar_expect_tx(bars + B_OBLOB * 8, pass ? 30720 : 40960);
                    flag_wait(&g_flag_o[rb * 2 + pass], epoch * 4u);
                    fence_async_glob();
                    for (int i = pass; i < 4; i++)
                        bulk_load(sb + XN_OFF + i * 10240, (const char*)g_o + (size_t)(rb * 8 + pass * 4 + ((cb + i) & 3)) * 10240, 10240, bars + B_OBLOB * 8);
                    if (pass == 0) {
                        mbar_expect_tx(bars + B_XT * 8, 64 * 320);
#pragma unroll 1
                        for (int i = 0; i < 64; i++) bulk_load(sb + XT_OFF + i * 336, P.x + (size_t)(rb * 64 + i) * 640 + cb * 160, 320, bars + B_XT * 8);
                    }
                }
                g_epoch[bid] = epoch;
            }
        }
    }
}

typedef CUresult (*EncodeFn)(CUtensorMap*, CUtensorMapDataType, cuuint32_t, void*, const cuuint64_t*, const cuuint64_t*, const cuuint32_t*,
                             const cuuint32_t*, CUtensorMapInterleave, CUtensorMapSwizzle, CUtensorMapL2promotion, CUtensorMapFloatOOBfill);

static void make_map(EncodeFn enc, CUtensorMap* m, const void* base, int K, int N, int grp, int boxk, int ngrp, CUtensorMapSwizzle sw) {
    cuuint32_t es[3] = {1, 1, 1};
    if (ngrp == 0) {
        cuuint64_t dims[2] = {(cuuint64_t)N, (cuuint64_t)K};
        cuuint64_t str[1] = {(cuuint64_t)N * 2};
        cuuint32_t box[2] = {(cuuint32_t)grp, (cuuint32_t)boxk};
        enc(m, CU_TENSOR_MAP_DATA_TYPE_BFLOAT16, 2, (void*)base, dims, str, box, es, CU_TENSOR_MAP_INTERLEAVE_NONE, sw,
            CU_TENSOR_MAP_L2_PROMOTION_L2_128B, CU_TENSOR_MAP_FLOAT_OOB_FILL_NONE);
    } else {
        cuuint64_t dims[3] = {(cuuint64_t)grp, (cuuint64_t)K, (cuuint64_t)(N / grp)};
        cuuint64_t str[2] = {(cuuint64_t)N * 2, (cuuint64_t)grp * 2};
        cuuint32_t box[3] = {(cuuint32_t)grp, (cuuint32_t)boxk, (cuuint32_t)ngrp};
        enc(m, CU_TENSOR_MAP_DATA_TYPE_BFLOAT16, 3, (void*)base, dims, str, box, es, CU_TENSOR_MAP_INTERLEAVE_NONE, sw,
            CU_TENSOR_MAP_L2_PROMOTION_L2_128B, CU_TENSOR_MAP_FLOAT_OOB_FILL_NONE);
    }
}

}

extern "C" void kernel_launch(void* const* d_in, const int* in_sizes, int n_in, void* d_out, int out_size) {
    using namespace mk;
    void* fn = nullptr;
    cudaDriverEntryPointQueryResult qr;
    cudaGetDriverEntryPoint("cuTensorMapEncodeTiled", &fn, cudaEnableDefault, &qr);
    EncodeFn enc = (EncodeFn)fn;
    Params P;
    P.x = (const __nv_bfloat16*)d_in[0]; P.wq = (const __nv_bfloat16*)d_in[1]; P.wk = (const __nv_bfloat16*)d_in[2];
    P.wv = (const __nv_bfloat16*)d_in[3]; P.wo = (const __nv_bfloat16*)d_in[4]; P.wg = (const __nv_bfloat16*)d_in[6];
    P.wu = (const __nv_bfloat16*)d_in[7]; P.wd = (const __nv_bfloat16*)d_in[8]; P.out = (__nv_bfloat16*)d_out;
    cudaGetSymbolAddress((void**)&P.s, g_scratch);
    CUtensorMap tq, tq32, tg, tu, td, to;
    make_map(enc, &tq, P.wq, 640, 640, 64, 64, 0, CU_TENSOR_MAP_SWIZZLE_128B);
    make_map(enc, &tq32, P.wq, 640, 640, 32, 160, 3, CU_TENSOR_MAP_SWIZZLE_64B);
    make_map(enc, &tg, P.wg, 640, 1536, 64, 64, 2, CU_TENSOR_MAP_SWIZZLE_128B);
    make_map(enc, &tu, P.wu, 640, 1536, 64, 64, 2, CU_TENSOR_MAP_SWIZZLE_128B);
    make_map(enc, &td, P.wd, 1536, 640, 64, 64, 0, CU_TENSOR_MAP_SWIZZLE_128B);
    make_map(enc, &to, P.wo, 640, 640, 32, 80, 5, CU_TENSOR_MAP_SWIZZLE_64B);
    cudaFuncSetAttribute(fused_kernel, cudaFuncAttributeMaxDynamicSharedMemorySize, SMEM_TOTAL);
    fused_kernel<<<128, 512, SMEM_TOTAL, cudaStreamPerThread>>>(P, tq, tq32, tg, tu, td, to);
}
```

```cpp
#include <cuda_runtime.h>
#include <cuda_bf16.h>
#include <cuda.h>
#include <stdint.h>

#define SLAB_DELAY 1800u
#define BMASK 0xE6u
#define LP 0
#define LN 2
#define EA 0
#define DEPN 3
#define DEPI 4
#define DEPH 3
#define SP 0
#define PST 6500u
#define FS 264
#define TWO 1
#define FH 1
#define PFB B_KVALL
#define PER 1
#define PACK_DELAY 13000u
#define QG 4
#define QD 0
#define FG 1
#define FD 1
#define DG 1
#define DD 1
#define WG_ 1
#define WD 1
#define NRA 168
#define NRG 152
#define XJ 0
#define DEF 0
#define NRE 144
#define LATEW 0
#define UD 5
#define RINGWAIT 3

#define KVTILE(g) (((rb & ~(PER - 1)) + (g)) & 31)
namespace mk {

constexpr uint32_t XN_OFF = 0, RING_OFF = 81920, HST_OFF = 180224, QO_OFF = 196608, KVR_OFF = 206848, BAR_OFF = 231424,
                   SMEM_TOTAL = 232448;
constexpr uint32_t WRAW_OFF = 204800, WKV_OFF = RING_OFF + 92160;
constexpr uint32_t SLOT0 = RING_OFF - 65536;
constexpr uint32_t XT_OFF = SLOT0 + 28672;
enum { B_SLAB = 0, B_SLABFREE = 1, B_KVFULL = 2, B_KVALL = 6, B_RING = 7, B_Q2 = 12, B_OREADY = 13,
       B_KVEMPTY = 15, B_REMPTY = 19, B_HFULL = 24, B_HFREE = 25, B_WKV = 26, B_SLAB2 = 27, B_PACK = 28, B_X = 14, B_HALF = 30, B_Y = 29 };
#define Y_OFF(w) ((w) < 3 ? HST_OFF + (w) * 5376 : XN_OFF)
#define S_OFF(w) (SLOT0 + (w) * 5376)

struct Scratch {
    uint4 kv[32 * 6144 / 16];
    uint4 h[32 * 24 * 8192 / 16];
    uint4 o[32 * 4 * 10240 / 16];
    uint4 op[128 * 640];
    uint4 w[4 * 136 * 5120 / 16];
    unsigned flag_kv[32 * FS], flag_h[96 * FH], flag_o[32 * FH], epoch[128], flag_w[4 * FH];
};
__device__ __align__(1024) Scratch g_scratch;
#define g_kv (P.s->kv)
#define g_h (P.s->h)
#define g_o (P.s->o)
#define g_w (P.s->w)
#define g_flag_w (P.s->flag_w)
#define g_flag_kv (P.s->flag_kv)
#define g_flag_h (P.s->flag_h)
#define g_flag_o (P.s->flag_o)
#define g_epoch (P.s->epoch)
#define PROF(i)
#define PROFW(i)
#define PROFV(i, v)
#define PW_BEGIN()
#define PW_END(acc)

__device__ __forceinline__ void wgmma_rs_n160_t1(float (&d)[80], uint32_t a0, uint32_t a1, uint32_t a2, uint32_t a3, uint64_t desc, int scale_d) {
    asm volatile("{\n.reg .pred p;\nsetp.ne.b32 p, %85, 0;\n"
        "wgmma.mma_async.sync.aligned.m64n160k16.f32.bf16.bf16 {%0, %1, %2, %3, %4, %5, %6, %7, %8, %9, %10, %11, %12, %13, %14, %15, %16, %17, %18, %19, %20, %21, %22, %23, %24, %25, %26, %27, %28, %29, %30, %31, %32, %33, %34, %35, %36, %37, %38, %39, %40, %41, %42, %43, %44, %45, %46, %47, %48, %49, %50, %51, %52, %53, %54, %55, %56, %57, %58, %59, %60, %61, %62, %63, %64, %65, %66, %67, %68, %69, %70, %71, %72, %73, %74, %75, %76, %77, %78, %79}, {%80, %81, %82, %83}, %84, p, 1, 1, 1;\n}\n"
        : "+f"(d[0]), "+f"(d[1]), "+f"(d[2]), "+f"(d[3]), "+f"(d[4]), "+f"(d[5]), "+f"(d[6]), "+f"(d[7]), "+f"(d[8]), "+f"(d[9]), "+f"(d[10]), "+f"(d[11]), "+f"(d[12]), "+f"(d[13]), "+f"(d[14]), "+f"(d[15]), "+f"(d[16]), "+f"(d[17]), "+f"(d[18]), "+f"(d[19]), "+f"(d[20]), "+f"(d[21]), "+f"(d[22]), "+f"(d[23]), "+f"(d[24]), "+f"(d[25]), "+f"(d[26]), "+f"(d[27]), "+f"(d[28]), "+f"(d[29]), "+f"(d[30]), "+f"(d[31]), "+f"(d[32]), "+f"(d[33]), "+f"(d[34]), "+f"(d[35]), "+f"(d[36]), "+f"(d[37]), "+f"(d[38]), "+f"(d[39]), "+f"(d[40]), "+f"(d[41]), "+f"(d[42]), "+f"(d[43]), "+f"(d[44]), "+f"(d[45]), "+f"(d[46]), "+f"(d[47]), "+f"(d[48]), "+f"(d[49]), "+f"(d[50]), "+f"(d[51]), "+f"(d[52]), "+f"(d[53]), "+f"(d[54]), "+f"(d[55]), "+f"(d[56]), "+f"(d[57]), "+f"(d[58]), "+f"(d[59]), "+f"(d[60]), "+f"(d[61]), "+f"(d[62]), "+f"(d[63]), "+f"(d[64]), "+f"(d[65]), "+f"(d[66]), "+f"(d[67]), "+f"(d[68]), "+f"(d[69]), "+f"(d[70]), "+f"(d[71]), "+f"(d[72]), "+f"(d[73]), "+f"(d[74]), "+f"(d[75]), "+f"(d[76]), "+f"(d[77]), "+f"(d[78]), "+f"(d[79])
        : "r"(a0), "r"(a1), "r"(a2), "r"(a3), "l"(desc), "r"(scale_d));
}
__device__ __forceinline__ void wgmma_rs_n24_t1(float (&d)[12], uint32_t a0, uint32_t a1, uint32_t a2, uint32_t a3, uint64_t desc, int scale_d) {
    asm volatile("{\n.reg .pred p;\nsetp.ne.b32 p, %17, 0;\n"
        "wgmma.mma_async.sync.aligned.m64n24k16.f32.bf16.bf16 {%0, %1, %2, %3, %4, %5, %6, %7, %8, %9, %10, %11}, {%12, %13, %14, %15}, %16, p, 1, 1, 1;\n}\n"
        : "+f"(d[0]), "+f"(d[1]), "+f"(d[2]), "+f"(d[3]), "+f"(d[4]), "+f"(d[5]), "+f"(d[6]), "+f"(d[7]), "+f"(d[8]), "+f"(d[9]), "+f"(d[10]), "+f"(d[11])
        : "r"(a0), "r"(a1), "r"(a2), "r"(a3), "l"(desc), "r"(scale_d));
}
__device__ __forceinline__ void wgmma_rs_n64_t0(float (&d)[32], uint32_t a0, uint32_t a1, uint32_t a2, uint32_t a3, uint64_t desc, int scale_d) {
    asm volatile("{\n.reg .pred p;\nsetp.ne.b32 p, %37, 0;\n"
        "wgmma.mma_async.sync.aligned.m64n64k16.f32.bf16.bf16 {%0, %1, %2, %3, %4, %5, %6, %7, %8, %9, %10, %11, %12, %13, %14, %15, %16, %17, %18, %19, %20, %21, %22, %23, %24, %25, %26, %27, %28, %29, %30, %31}, {%32, %33, %34, %35}, %36, p, 1, 1, 0;\n}\n"
        : "+f"(d[0]), "+f"(d[1]), "+f"(d[2]), "+f"(d[3]), "+f"(d[4]), "+f"(d[5]), "+f"(d[6]), "+f"(d[7]), "+f"(d[8]), "+f"(d[9]), "+f"(d[10]), "+f"(d[11]), "+f"(d[12]), "+f"(d[13]), "+f"(d[14]), "+f"(d[15]), "+f"(d[16]), "+f"(d[17]), "+f"(d[18]), "+f"(d[19]), "+f"(d[20]), "+f"(d[21]), "+f"(d[22]), "+f"(d[23]), "+f"(d[24]), "+f"(d[25]), "+f"(d[26]), "+f"(d[27]), "+f"(d[28]), "+f"(d[29]), "+f"(d[30]), "+f"(d[31])
        : "r"(a0), "r"(a1), "r"(a2), "r"(a3), "l"(desc), "r"(scale_d));
}
__device__ __forceinline__ void wgmma_ss_n24(float (&d)[12], uint64_t da, uint64_t db, int scale_d) {
    asm volatile("{\n.reg .pred p;\nsetp.ne.b32 p, %14, 0;\n"
        "wgmma.mma_async.sync.aligned.m64n24k16.f32.bf16.bf16 {%0, %1, %2, %3, %4, %5, %6, %7, %8, %9, %10, %11}, %12, %13, p, 1, 1, 0, 1;\n}\n"
        : "+f"(d[0]), "+f"(d[1]), "+f"(d[2]), "+f"(d[3]), "+f"(d[4]), "+f"(d[5]), "+f"(d[6]), "+f"(d[7]), "+f"(d[8]), "+f"(d[9]), "+f"(d[10]), "+f"(d[11])
        : "l"(da), "l"(db), "r"(scale_d));
}
__device__ __forceinline__ void wgmma_ss_n48(float (&d)[24], uint64_t da, uint64_t db, int scale_d) {
    asm volatile("{\n.reg .pred p;\nsetp.ne.b32 p, %26, 0;\n"
        "wgmma.mma_async.sync.aligned.m64n48k16.f32.bf16.bf16 {%0, %1, %2, %3, %4, %5, %6, %7, %8, %9, %10, %11, %12, %13, %14, %15, %16, %17, %18, %19, %20, %21, %22, %23}, %24, %25, p, 1, 1, 0, 1;\n}\n"
        : "+f"(d[0]), "+f"(d[1]), "+f"(d[2]), "+f"(d[3]), "+f"(d[4]), "+f"(d[5]), "+f"(d[6]), "+f"(d[7]), "+f"(d[8]), "+f"(d[9]), "+f"(d[10]), "+f"(d[11]), "+f"(d[12]), "+f"(d[13]), "+f"(d[14]), "+f"(d[15]), "+f"(d[16]), "+f"(d[17]), "+f"(d[18]), "+f"(d[19]), "+f"(d[20]), "+f"(d[21]), "+f"(d[22]), "+f"(d[23])
        : "l"(da), "l"(db), "r"(scale_d));
}
__device__ __forceinline__ void wgmma_ss_n96(float (&d)[48], uint64_t da, uint64_t db, int scale_d) {
    asm volatile("{\n.reg .pred p;\nsetp.ne.b32 p, %50, 0;\n"
        "wgmma.mma_async.sync.aligned.m64n96k16.f32.bf16.bf16 {%0, %1, %2, %3, %4, %5, %6, %7, %8, %9, %10, %11, %12, %13, %14, %15, %16, %17, %18, %19, %20, %21, %22, %23, %24, %25, %26, %27, %28, %29, %30, %31, %32, %33, %34, %35, %36, %37, %38, %39, %40, %41, %42, %43, %44, %45, %46, %47}, %48, %49, p, 1, 1, 0, 1;\n}\n"
        : "+f"(d[0]), "+f"(d[1]), "+f"(d[2]), "+f"(d[3]), "+f"(d[4]), "+f"(d[5]), "+f"(d[6]), "+f"(d[7]), "+f"(d[8]), "+f"(d[9]), "+f"(d[10]), "+f"(d[11]), "+f"(d[12]), "+f"(d[13]), "+f"(d[14]), "+f"(d[15]), "+f"(d[16]), "+f"(d[17]), "+f"(d[18]), "+f"(d[19]), "+f"(d[20]), "+f"(d[21]), "+f"(d[22]), "+f"(d[23]), "+f"(d[24]), "+f"(d[25]), "+f"(d[26]), "+f"(d[27]), "+f"(d[28]), "+f"(d[29]), "+f"(d[30]), "+f"(d[31]), "+f"(d[32]), "+f"(d[33]), "+f"(d[34]), "+f"(d[35]), "+f"(d[36]), "+f"(d[37]), "+f"(d[38]), "+f"(d[39]), "+f"(d[40]), "+f"(d[41]), "+f"(d[42]), "+f"(d[43]), "+f"(d[44]), "+f"(d[45]), "+f"(d[46]), "+f"(d[47])
        : "l"(da), "l"(db), "r"(scale_d));
}
__device__ __forceinline__ void wgmma_ss_n128(float (&d)[64], uint64_t da, uint64_t db, int scale_d) {
    asm volatile("{\n.reg .pred p;\nsetp.ne.b32 p, %66, 0;\n"
        "wgmma.mma_async.sync.aligned.m64n128k16.f32.bf16.bf16 {%0, %1, %2, %3, %4, %5, %6, %7, %8, %9, %10, %11, %12, %13, %14, %15, %16, %17, %18, %19, %20, %21, %22, %23, %24, %25, %26, %27, %28, %29, %30, %31, %32, %33, %34, %35, %36, %37, %38, %39, %40, %41, %42, %43, %44, %45, %46, %47, %48, %49, %50, %51, %52, %53, %54, %55, %56, %57, %58, %59, %60, %61, %62, %63}, %64, %65, p, 1, 1, 0, 1;\n}\n"
        : "+f"(d[0]), "+f"(d[1]), "+f"(d[2]), "+f"(d[3]), "+f"(d[4]), "+f"(d[5]), "+f"(d[6]), "+f"(d[7]), "+f"(d[8]), "+f"(d[9]), "+f"(d[10]), "+f"(d[11]), "+f"(d[12]), "+f"(d[13]), "+f"(d[14]), "+f"(d[15]), "+f"(d[16]), "+f"(d[17]), "+f"(d[18]), "+f"(d[19]), "+f"(d[20]), "+f"(d[21]), "+f"(d[22]), "+f"(d[23]), "+f"(d[24]), "+f"(d[25]), "+f"(d[26]), "+f"(d[27]), "+f"(d[28]), "+f"(d[29]), "+f"(d[30]), "+f"(d[31]), "+f"(d[32]), "+f"(d[33]), "+f"(d[34]), "+f"(d[35]), "+f"(d[36]), "+f"(d[37]), "+f"(d[38]), "+f"(d[39]), "+f"(d[40]), "+f"(d[41]), "+f"(d[42]), "+f"(d[43]), "+f"(d[44]), "+f"(d[45]), "+f"(d[46]), "+f"(d[47]), "+f"(d[48]), "+f"(d[49]), "+f"(d[50]), "+f"(d[51]), "+f"(d[52]), "+f"(d[53]), "+f"(d[54]), "+f"(d[55]), "+f"(d[56]), "+f"(d[57]), "+f"(d[58]), "+f"(d[59]), "+f"(d[60]), "+f"(d[61]), "+f"(d[62]), "+f"(d[63])
        : "l"(da), "l"(db), "r"(scale_d));
}
__device__ __forceinline__ void wgmma_ss_n160(float (&d)[80], uint64_t da, uint64_t db, int scale_d) {
    asm volatile("{\n.reg .pred p;\nsetp.ne.b32 p, %82, 0;\n"
        "wgmma.mma_async.sync.aligned.m64n160k16.f32.bf16.bf16 {%0, %1, %2, %3, %4, %5, %6, %7, %8, %9, %10, %11, %12, %13, %14, %15, %16, %17, %18, %19, %20, %21, %22, %23, %24, %25, %26, %27, %28, %29, %30, %31, %32, %33, %34, %35, %36, %37, %38, %39, %40, %41, %42, %43, %44, %45, %46, %47, %48, %49, %50, %51, %52, %53, %54, %55, %56, %57, %58, %59, %60, %61, %62, %63, %64, %65, %66, %67, %68, %69, %70, %71, %72, %73, %74, %75, %76, %77, %78, %79}, %80, %81, p, 1, 1, 0, 1;\n}\n"
        : "+f"(d[0]), "+f"(d[1]), "+f"(d[2]), "+f"(d[3]), "+f"(d[4]), "+f"(d[5]), "+f"(d[6]), "+f"(d[7]), "+f"(d[8]), "+f"(d[9]), "+f"(d[10]), "+f"(d[11]), "+f"(d[12]), "+f"(d[13]), "+f"(d[14]), "+f"(d[15]), "+f"(d[16]), "+f"(d[17]), "+f"(d[18]), "+f"(d[19]), "+f"(d[20]), "+f"(d[21]), "+f"(d[22]), "+f"(d[23]), "+f"(d[24]), "+f"(d[25]), "+f"(d[26]), "+f"(d[27]), "+f"(d[28]), "+f"(d[29]), "+f"(d[30]), "+f"(d[31]), "+f"(d[32]), "+f"(d[33]), "+f"(d[34]), "+f"(d[35]), "+f"(d[36]), "+f"(d[37]), "+f"(d[38]), "+f"(d[39]), "+f"(d[40]), "+f"(d[41]), "+f"(d[42]), "+f"(d[43]), "+f"(d[44]), "+f"(d[45]), "+f"(d[46]), "+f"(d[47]), "+f"(d[48]), "+f"(d[49]), "+f"(d[50]), "+f"(d[51]), "+f"(d[52]), "+f"(d[53]), "+f"(d[54]), "+f"(d[55]), "+f"(d[56]), "+f"(d[57]), "+f"(d[58]), "+f"(d[59]), "+f"(d[60]), "+f"(d[61]), "+f"(d[62]), "+f"(d[63]), "+f"(d[64]), "+f"(d[65]), "+f"(d[66]), "+f"(d[67]), "+f"(d[68]), "+f"(d[69]), "+f"(d[70]), "+f"(d[71]), "+f"(d[72]), "+f"(d[73]), "+f"(d[74]), "+f"(d[75]), "+f"(d[76]), "+f"(d[77]), "+f"(d[78]), "+f"(d[79])
        : "l"(da), "l"(db), "r"(scale_d));
}

__device__ __forceinline__ uint32_t smem_u32(const void* p) { return (uint32_t)__cvta_generic_to_shared(p); }
__device__ __forceinline__ void wg_fence() { asm volatile("wgmma.fence.sync.aligned;" ::: "memory"); }
__device__ __forceinline__ void wg_commit() { asm volatile("wgmma.commit_group.sync.aligned;" ::: "memory"); }
template <int N> __device__ __forceinline__ void wg_wait() { asm volatile("wgmma.wait_group.sync.aligned %0;" :: "n"(N) : "memory"); }
__device__ __forceinline__ uint64_t mkdesc(uint32_t addr, uint32_t lbo, uint32_t sbo, uint32_t mode) {
    return (uint64_t)((addr & 0x3FFFF) >> 4) | ((uint64_t)(lbo >> 4) << 16) | ((uint64_t)(sbo >> 4) << 32) | ((uint64_t)mode << 62);
}
__device__ __forceinline__ void mbar_init(uint32_t bar, int cnt) { asm volatile("mbarrier.init.shared::cta.b64 [%0], %1;" :: "r"(bar), "r"(cnt) : "memory"); }
__device__ __forceinline__ void mbar_expect_tx(uint32_t bar, uint32_t bytes) { asm volatile("mbarrier.arrive.expect_tx.shared::cta.b64 _, [%0], %1;" :: "r"(bar), "r"(bytes) : "memory"); }
__device__ __forceinline__ void mbar_arrive(uint32_t bar) { asm volatile("mbarrier.arrive.shared::cta.b64 _, [%0];" :: "r"(bar) : "memory"); }
__device__ __forceinline__ bool mbar_try(uint32_t bar, uint32_t parity) {
    uint32_t ok;
    asm volatile("{\n.reg .pred p;\nmbarrier.try_wait.parity.shared::cta.b64 p, [%1], %2;\nselp.b32 %0, 1, 0, p;\n}" : "=r"(ok) : "r"(bar), "r"(parity) : "memory");
    return ok != 0;
}
__device__ __forceinline__ bool mbar_test(uint32_t bar, uint32_t parity) {
    uint32_t ok;
    asm volatile("{\n.reg .pred p;\nmbarrier.test_wait.parity.shared::cta.b64 p, [%1], %2;\nselp.b32 %0, 1, 0, p;\n}" : "=r"(ok) : "r"(bar), "r"(parity) : "memory");
    return ok != 0;
}
__device__ __forceinline__ void mbar_wait(uint32_t bar, uint32_t parity) {
    asm volatile("{\n.reg .pred p;\n.reg .u32 n;\nmov.u32 n, 0;\n"
                 "WL:\nmbarrier.try_wait.parity.shared::cta.b64 p, [%0], %1;\n@p bra WD;\n"
                 "add.u32 n, n, 1;\nsetp.lt.u32 p, n, 2000000;\n@p bra WL;\ntrap;\nWD:\n}" :: "r"(bar), "r"(parity) : "memory");
}
__device__ __forceinline__ void mbar_arrive_if(uint32_t bar, bool pred) {
    asm volatile("{\n.reg .pred p;\nsetp.ne.u32 p, %1, 0;\n@p mbarrier.arrive.shared::cta.b64 _, [%0];\n}" :: "r"(bar), "r"((uint32_t)pred) : "memory");
}
__device__ __forceinline__ uint32_t ld_acquire(const unsigned* p) { uint32_t v; asm volatile("ld.acquire.gpu.global.u32 %0, [%1];" : "=r"(v) : "l"(p) : "memory"); return v; }
__device__ __forceinline__ void red_release(unsigned* p) { asm volatile("red.release.gpu.global.add.u32 [%0], 1;" :: "l"(p) : "memory"); }
__device__ __forceinline__ void flag_wait(const unsigned* p, uint32_t target) {
    uint32_t it = 0;
    while ((int)(ld_acquire(p) - target) < 0) { if (++it > 4000000u) __trap(); }
}
__device__ __forceinline__ void fence_async_glob() { asm volatile("fence.proxy.async.global;" ::: "memory"); }
__device__ __forceinline__ void fence_async_smem() { asm volatile("fence.proxy.async.shared::cta;" ::: "memory"); }
__device__ __forceinline__ void bar_sync(int id, int n) { asm volatile("bar.sync %0, %1;" :: "r"(id), "r"(n) : "memory"); }
__device__ __forceinline__ void bulk_load(uint32_t dst, const void* src, uint32_t bytes, uint32_t bar) {
    asm volatile("cp.async.bulk.shared::cluster.global.mbarrier::complete_tx::bytes [%0], [%1], %2, [%3];" :: "r"(dst), "l"(src), "r"(bytes), "r"(bar) : "memory");
}
__device__ __forceinline__ void bulk_store(void* dst, uint32_t src, uint32_t bytes) {
    asm volatile("cp.async.bulk.global.shared::cta.bulk_group [%0], [%1], %2;" :: "l"(dst), "r"(src), "r"(bytes) : "memory");
}
__device__ __forceinline__ void bulk_commit_wait() {
    asm volatile("cp.async.bulk.commit_group;" ::: "memory");
    asm volatile("cp.async.bulk.wait_group 0;" ::: "memory");
}
__device__ __forceinline__ void l2_prefetch(const void* src, uint32_t bytes) { asm volatile("cp.async.bulk.prefetch.L2.global [%0], %1;" :: "l"(src), "r"(bytes) : "memory"); }
__device__ __forceinline__ void tma2d(uint32_t dst, const CUtensorMap* tm, int c0, int c1, uint32_t bar) {
    asm volatile("cp.async.bulk.tensor.2d.shared::cluster.global.mbarrier::complete_tx::bytes [%0], [%1, {%3, %4}], [%2];"
                 :: "r"(dst), "l"(tm), "r"(bar), "r"(c0), "r"(c1) : "memory");
}
__device__ __forceinline__ void tma3d(uint32_t dst, const CUtensorMap* tm, int c0, int c1, int c2, uint32_t bar) {
    asm volatile("cp.async.bulk.tensor.3d.shared::cluster.global.mbarrier::complete_tx::bytes [%0], [%1, {%3, %4, %5}], [%2];"
                 :: "r"(dst), "l"(tm), "r"(bar), "r"(c0), "r"(c1), "r"(c2) : "memory");
}
__device__ __forceinline__ void tma4d(uint32_t dst, const CUtensorMap* tm, int c0, int c1, int c2, int c3, uint32_t bar) {
    asm volatile("cp.async.bulk.tensor.4d.shared::cluster.global.mbarrier::complete_tx::bytes [%0], [%1, {%3, %4, %5, %6}], [%2];"
                 :: "r"(dst), "l"(tm), "r"(bar), "r"(c0), "r"(c1), "r"(c2), "r"(c3) : "memory");
}
__device__ __forceinline__ void sts32(uint32_t a, uint32_t v) { asm volatile("st.shared.b32 [%0], %1;" :: "r"(a), "r"(v) : "memory"); }
__device__ __forceinline__ uint32_t lds32(uint32_t a) { uint32_t v; asm volatile("ld.shared.b32 %0, [%1];" : "=r"(v) : "r"(a) : "memory"); return v; }
__device__ __forceinline__ void sts128(uint32_t a, uint32_t x, uint32_t y, uint32_t z, uint32_t w) { asm volatile("st.shared.v4.b32 [%0], {%1, %2, %3, %4};" :: "r"(a), "r"(x), "r"(y), "r"(z), "r"(w) : "memory"); }
__device__ __forceinline__ void stsm4(uint32_t a, uint32_t x, uint32_t y, uint32_t z, uint32_t w) { asm volatile("stmatrix.sync.aligned.m8n8.x4.shared.b16 [%0], {%1, %2, %3, %4};" :: "r"(a), "r"(x), "r"(y), "r"(z), "r"(w) : "memory"); }
__device__ __forceinline__ void ldsm4(uint32_t a, uint32_t& x, uint32_t& y, uint32_t& z, uint32_t& w) { asm volatile("ldmatrix.sync.aligned.m8n8.x4.shared.b16 {%0, %1, %2, %3}, [%4];" : "=r"(x), "=r"(y), "=r"(z), "=r"(w) : "r"(a) : "memory"); }
__device__ __forceinline__ float ex2(float x) { float y; asm("ex2.approx.ftz.f32 %0, %1;" : "=f"(y) : "f"(x)); return y; }
__device__ __forceinline__ float rcp(float x) { float y; asm("rcp.approx.ftz.f32 %0, %1;" : "=f"(y) : "f"(x)); return y; }
__device__ __forceinline__ uint32_t pack_bf16(float lo, float hi) { uint32_t r; asm("cvt.rn.bf16x2.f32 %0, %1, %2;" : "=r"(r) : "f"(hi), "f"(lo)); return r; }
__device__ __forceinline__ float bf_lo(uint32_t v) { return __uint_as_float(v << 16); }
__device__ __forceinline__ float bf_hi(uint32_t v) { return __uint_as_float(v & 0xffff0000u); }
__device__ __forceinline__ float bf_round(float x) { return bf_lo(pack_bf16(x, 0.f)); }
__device__ __forceinline__ uint32_t bf2_sub(uint32_t a, uint32_t b) { uint32_t r; asm("sub.rn.bf16x2 %0, %1, %2;" : "=r"(r) : "r"(a), "r"(b)); return r; }
__device__ __forceinline__ uint32_t bf2_add(uint32_t a, uint32_t b) { uint32_t r; asm("add.rn.bf16x2 %0, %1, %2;" : "=r"(r) : "r"(a), "r"(b)); return r; }
__device__ __forceinline__ uint32_t bf2_mul(uint32_t a, uint32_t b) { uint32_t r; asm("mul.rn.bf16x2 %0, %1, %2;" : "=r"(r) : "r"(a), "r"(b)); return r; }

__device__ __forceinline__ uint32_t bf2_fma(uint32_t a, uint32_t b, uint32_t c) { uint32_t r; asm("fma.rn.bf16x2 %0, %1, %2, %3;" : "=r"(r) : "r"(a), "r"(b), "r"(c)); return r; }
__device__ __forceinline__ void mma16816(float (&d)[4], uint32_t a0, uint32_t a1, uint32_t a2, uint32_t a3, uint32_t b0, uint32_t b1) {
    asm("mma.sync.aligned.m16n8k16.row.col.f32.bf16.bf16.f32 {%0, %1, %2, %3}, {%4, %5, %6, %7}, {%8, %9}, {%0, %1, %2, %3};"
        : "+f"(d[0]), "+f"(d[1]), "+f"(d[2]), "+f"(d[3]) : "r"(a0), "r"(a1), "r"(a2), "r"(a3), "r"(b0), "r"(b1));
}
__device__ __forceinline__ uint4 ldg128(const void* p) { uint4 v; asm volatile("ld.global.nc.L1::no_allocate.v4.u32 {%0, %1, %2, %3}, [%4];" : "=r"(v.x), "=r"(v.y), "=r"(v.z), "=r"(v.w) : "l"(p)); return v; }
__device__ __forceinline__ uint4 ldg128o(const void* p) { uint4 v; asm volatile("ld.global.L1::no_allocate.v4.u32 {%0, %1, %2, %3}, [%4];" : "=r"(v.x), "=r"(v.y), "=r"(v.z), "=r"(v.w) : "l"(p) : "memory"); return v; }
__device__ __forceinline__ void st_pkt(uint4* p, uint32_t x, uint32_t y, uint32_t z, uint32_t w) {
    asm volatile("st.relaxed.gpu.global.v4.u32 [%0], {%1, %2, %3, %4};" :: "l"(p), "r"(x), "r"(y), "r"(z), "r"(w) : "memory");
}
__device__ __forceinline__ void st_pkt2(void* p, uint32_t x, uint32_t y) {
    asm volatile("st.relaxed.gpu.global.v2.u32 [%0], {%1, %2};" :: "l"(p), "r"(x), "r"(y) : "memory");
}
__device__ __forceinline__ uint4 ld_pkt(const uint4* p) { uint4 v; asm volatile("ld.relaxed.gpu.global.v4.u32 {%0, %1, %2, %3}, [%4];" : "=r"(v.x), "=r"(v.y), "=r"(v.z), "=r"(v.w) : "l"(p) : "memory"); return v; }
__device__ __forceinline__ bool bar_and(int id, int n, bool v) {
    uint32_t r;
    asm volatile("{\n.reg .pred p, q;\nsetp.ne.u32 p, %3, 0;\nbarrier.cta.red.and.aligned.pred q, %1, %2, p;\nselp.b32 %0, 1, 0, q;\n}" : "=r"(r) : "r"(id), "r"(n), "r"((uint32_t)v) : "memory");
    return r != 0;
}
__device__ __forceinline__ bool elect() { uint32_t r; asm volatile("{\n.reg .pred p;\nelect.sync _|p, 0xffffffff;\nselp.b32 %0, 1, 0, p;\n}" : "=r"(r)); return r != 0; }
__device__ __forceinline__ int fresh_tid() { int t; asm volatile("mov.u32 %0, %tid.x;" : "=r"(t)); return t; }
__device__ __forceinline__ uint2 lds64(uint32_t a) { uint2 v; asm volatile("ld.shared.v2.u32 {%0, %1}, [%2];" : "=r"(v.x), "=r"(v.y) : "r"(a) : "memory"); return v; }
__device__ __forceinline__ void sts64(uint32_t a, uint32_t x, uint32_t y) { asm volatile("st.shared.v2.b32 [%0], {%1, %2};" :: "r"(a), "r"(x), "r"(y) : "memory"); }
__device__ __forceinline__ uint4 lds128(uint32_t a) { uint4 v; asm volatile("ld.shared.v4.u32 {%0, %1, %2, %3}, [%4];" : "=r"(v.x), "=r"(v.y), "=r"(v.z), "=r"(v.w) : "r"(a) : "memory"); return v; }

__device__ __forceinline__ void exch(uint32_t& v, uint32_t a) { asm volatile("atom.shared.exch.b32 %0, [%1], %0;" : "+r"(v) : "r"(a) : "memory"); }
__device__ __forceinline__ uint32_t bf2_min(uint32_t a, uint32_t b) { uint32_t r; asm("min.bf16x2 %0, %1, %2;" : "=r"(r) : "r"(a), "r"(b)); return r; }
__device__ __forceinline__ uint32_t ex2_fix(float x0, float x1, uint32_t half) {
    uint32_t w;
    asm("cvt.pack.sat.s16.s32 %0, %1, %2;" : "=r"(w) : "r"(__float_as_uint(x1)), "r"(__float_as_uint(x0)));
    return bf2_fma(w, (w & 0x007F007Fu) | half, w & 0x7F807F80u);
}
#define FIXED(blk) ((BMASK >> ((blk) & (8 * PER - 1))) & 1u)
template <int C>
__device__ __forceinline__ void chunk(const float (&s)[32], uint32_t (&p)[16], uint32_t ec, int j) {
#pragma unroll
    for (int i = 4 * C; i < 4 * C + 4; i++)
        p[i] = FIXED(8 * j + (i >> 1)) ? ex2_fix(s[2 * i], s[2 * i + 1], ec) : pack_bf16(ex2(s[2 * i]), ex2(s[2 * i + 1]));
}
__device__ __forceinline__ void softexp(const float (&s)[32], uint32_t (&p)[16], uint32_t ec, bool dep) {
    uint32_t e2 = ec;
    int n = 0;
#pragma unroll
    for (int i = 0; i < 16; i++) if (!FIXED(i >> 1)) {
        p[i] = pack_bf16(ex2(s[2 * i]), ex2(s[2 * i + 1]));
        if (dep && n++ == DEPI) e2 = ec | (p[i] & 0x80008000u);
    }
    n = 2 * __popc(BMASK);
#pragma unroll
    for (int i = 0; i < 16; i++) if (FIXED(i >> 1)) p[i] = ex2_fix(s[2 * i], s[2 * i + 1], --n < DEPN ? e2 : ec);
}
#define PV(o, p, C, d) wgmma_rs_n24_t1(o, p[4 * C], p[4 * C + 1], p[4 * C + 2], p[4 * C + 3], (d) + 48 * C, 1)
#define QK0(s, q, d) wgmma_rs_n64_t0(s, q[0], q[1], q[2], q[3], d, 0)
#define QK1(s, q, d) wgmma_rs_n64_t0(s, q[4], q[5], q[6], q[7], (d) + 16, 1)

__device__ __noinline__ void attn_exact_row(const uint32_t* kv, uint32_t qo, int row, int col0) {
    float q[20], o[20];
#pragma unroll
    for (int d = 0; d < 20; d += 2) {
        const int col = col0 + d;
        uint32_t v = lds32(qo + (col >> 3) * 1024 + (row >> 3) * 128 + (row & 7) * 16 + (col & 7) * 2);
        q[d] = bf_lo(v) * 0x1p64f; q[d + 1] = bf_hi(v) * 0x1p64f; o[d] = 0.f; o[d + 1] = 0.f;
    }
    float m = -INFINITY, l = 0.f;
#pragma unroll 1
    for (int key = 0; key < 2048; key++) {
        const uint32_t* p = kv + (key >> 6) * 1536 + 768 + ((key >> 3) & 7) * 96 + (key & 7) * 4;
        const uint32_t* pk = kv + (((key >> 6) - 1) & 31) * 1536 + ((key >> 3) & 7) * 96 + (key & 7) * 4;
        float s = 0.f;
        const float ks = FIXED(key >> 3) ? 0x1p78f : 0x1p-64f;
#pragma unroll
        for (int d = 0; d < 20; d += 2) {
            uint32_t v = __ldcg(pk + (d >> 3) * 32 + ((d & 7) >> 1));
            s = fmaf(q[d], bf_lo(v) * ks, s); s = fmaf(q[d + 1], bf_hi(v) * ks, s);
        }
        const float mn = fmaxf(m, s);
        const float sc = exp2f(m - mn), e = exp2f(s - mn);
        m = mn; l = l * sc + e;
#pragma unroll
        for (int d = 0; d < 20; d += 2) {
            uint32_t v = __ldcg(p + (d >> 3) * 32 + ((d & 7) >> 1));
            o[d] = fmaf(e, bf_lo(v), o[d] * sc); o[d + 1] = fmaf(e, bf_hi(v), o[d + 1] * sc);
        }
    }
    const float il = 1.0f / l;
#pragma unroll
    for (int d = 0; d < 20; d += 2) {
        const int col = col0 + d;
        sts32(qo + (col >> 3) * 1024 + (row >> 3) * 128 + (row & 7) * 16 + (col & 7) * 2, pack_bf16(o[d] * il, o[d + 1] * il));
    }
}

template <int NV>
__device__ __forceinline__ void ln_rows(const uint4 (&v)[NV], int lane, uint32_t xa) {
    float a0[4] = {0.f, 0.f, 0.f, 0.f}, a1[4] = {0.f, 0.f, 0.f, 0.f};
#pragma unroll
    for (int t = 0; t < NV; t++) {
        mma16816(a0, v[t].x, 0x3F803F80u, v[t].y, 0x3F803F80u, v[t].x, v[t].y);
        mma16816(a1, v[t].z, 0x3F803F80u, v[t].w, 0x3F803F80u, v[t].z, v[t].w);
    }
    const float cs = (a0[2] + a0[3]) + (a1[2] + a1[3]);
    const float dg = (lane & 4) ? a0[1] + a1[1] : a0[0] + a1[0];
    float s, sq;
    if (NV == 5) {
        const int h = lane >> 4;
        s = __shfl_sync(~0u, cs, h * 2) + __shfl_sync(~0u, cs, h * 2 + 1);
        sq = (__shfl_sync(~0u, dg, h * 18) + __shfl_sync(~0u, dg, h * 18 + 4)) + (__shfl_sync(~0u, dg, h * 18 + 9) + __shfl_sync(~0u, dg, h * 18 + 13));
    } else {
        const int h = lane >> 3;
        s = __shfl_sync(~0u, cs, h);
        sq = __shfl_sync(~0u, dg, h * 9) + __shfl_sync(~0u, dg, h * 9 + 4);
    }
    const float mean = s * (1.0f / 640.0f);
    float var = fmaf(sq, 1.0f / 640.0f, -mean * mean);
    if (__any_sync(~0u, !(mean * mean <= 16.0f * var))) {
        float s0 = 0.f, s1 = 0.f;
#pragma unroll
        for (int t = 0; t < NV; t++) {
            float a;
            a = bf_lo(v[t].x) - mean; s0 = fmaf(a, a, s0); a = bf_hi(v[t].x) - mean; s1 = fmaf(a, a, s1);
            a = bf_lo(v[t].y) - mean; s0 = fmaf(a, a, s0); a = bf_hi(v[t].y) - mean; s1 = fmaf(a, a, s1);
            a = bf_lo(v[t].z) - mean; s0 = fmaf(a, a, s0); a = bf_hi(v[t].z) - mean; s1 = fmaf(a, a, s1);
            a = bf_lo(v[t].w) - mean; s0 = fmaf(a, a, s0); a = bf_hi(v[t].w) - mean; s1 = fmaf(a, a, s1);
        }
        s0 += s1;
#pragma unroll
        for (int o = 1; o < 80 / NV; o <<= 1) s0 += __shfl_xor_sync(~0u, s0, o);
        var = s0 * (1.0f / 640.0f);
    }
    float sd;
    asm("sqrt.approx.f32 %0, %1;" : "=f"(sd) : "f"(bf_round(bf_round(var) + 1e-5f)));
    const float rinv = rcp(bf_round(sd));
    const float rh = bf_round(rinv);
    const uint32_t m2 = pack_bf16(mean, mean), rh2 = pack_bf16(rh, rh), rl2 = pack_bf16(rinv - rh, rinv - rh);
#pragma unroll
    for (int t = 0; t < NV; t++) {
        const uint32_t d0 = bf2_sub(v[t].x, m2), d1 = bf2_sub(v[t].y, m2), d2 = bf2_sub(v[t].z, m2), d3 = bf2_sub(v[t].w, m2);
        sts128(xa + t * (81920 / NV), bf2_fma(d0, rh2, bf2_mul(d0, rl2)), bf2_fma(d1, rh2, bf2_mul(d1, rl2)),
               bf2_fma(d2, rh2, bf2_mul(d2, rl2)), bf2_fma(d3, rh2, bf2_mul(d3, rl2)));
    }
}

struct Params {
    const __nv_bfloat16 *x, *wk, *wv;
    Scratch* s;
    const __nv_bfloat16 *wq, *wo, *wg, *wu, *wd;
    __nv_bfloat16* out;
};

__global__ void __launch_bounds__(512, 1)
fused_kernel(const Params P, const __grid_constant__ CUtensorMap tm_wq, const __grid_constant__ CUtensorMap tm_wq32, const __grid_constant__ CUtensorMap tm_wg, const __grid_constant__ CUtensorMap tm_wu,
             const __grid_constant__ CUtensorMap tm_wd, const __grid_constant__ CUtensorMap tm_wo,
             const __grid_constant__ CUtensorMap tm_wdc, const __grid_constant__ CUtensorMap tm_woc,
             const __grid_constant__ CUtensorMap tm_x, const __grid_constant__ CUtensorMap tm_wor, const __grid_constant__ CUtensorMap tm_worc) {
    const uint32_t t_launch = (uint32_t)clock();
    extern __shared__ __align__(1024) char smem_raw[];
    const uint32_t sb = smem_u32(smem_raw);
    const uint32_t bars = sb + BAR_OFF;
    const int tid = threadIdx.x, lane = tid & 31;
    const int warp_id = __shfl_sync(~0u, tid >> 5, 0);
    const int wg = warp_id >> 2, warp = warp_id & 3;
    const int r = lane >> 2, c = lane & 3;
    const int bid = blockIdx.x;
    const int rb = bid >> 2, cb = bid & 3, rank = cb & 1;
    constexpr float QSCALE = 0.22360679774997896f * 1.4426950408889634f * 0x1p-64f;

    const int lrow = ((tid >> 3) ^ (rank << 5) ^ 32) & 63;
    const uint4* xr = (const uint4*)(P.x + (size_t)(rb * 64 + lrow) * 640) + (lane & 7);
    const uint32_t xa = sb + XN_OFF + lrow * 128 + (((lane ^ lrow) & 7) << 4);
    if (wg >= 2) {
        uint4 v[10];
#pragma unroll
        for (int t = 0; t < 10; t++) v[t] = ldg128(xr + 8 * t);
        PROF(42);
        ln_rows<10>(v, lane, xa);
        PROF(22 + wg);
        bar_sync(4, 512);
        PROF(27);
    }

    if (wg < 2) {
        if (tid == 0) {
            mbar_init(bars + B_WKV * 8, 1); mbar_init(bars + B_SLAB * 8, 1); mbar_init(bars + B_SLAB2 * 8, 1);
            asm volatile("fence.mbarrier_init.release.cluster;" ::: "memory");
            mbar_expect_tx(bars + B_WKV * 8, 25600);
            bulk_load(sb + WRAW_OFF, cb < 2 ? P.wk : P.wv, 25600, bars + B_WKV * 8);
            mbar_expect_tx(bars + B_SLAB * 8, 92160);
            asm volatile("prefetch.tensormap [%0];" :: "l"(&tm_wq32) : "memory");
        }
        if (tid == 32) {
            mbar_init(bars + B_SLABFREE * 8, 8); mbar_init(bars + B_HALF * 8, 8);
            for (int i = 0; i < 4; i++) { mbar_init(bars + (B_KVFULL + i) * 8, 1); mbar_init(bars + (B_KVEMPTY + i) * 8, 8); }
            for (int i = 0; i < 5; i++) { mbar_init(bars + (B_RING + i) * 8, 1); mbar_init(bars + (B_REMPTY + i) * 8, 4); }
            for (int i = 0; i < 3; i++) mbar_arrive(bars + (B_RING + i) * 8);
            for (int i = 0; i < 4; i++) mbar_arrive(bars + (B_REMPTY + 2) * 8);
            mbar_init(bars + B_KVALL * 8, 1); sts32(bars + 31 * 8, 0u);
            mbar_init(bars + B_Q2 * 8, 4); mbar_init(bars + B_OREADY * 8, 8);
            mbar_init(bars + B_PACK * 8, 1); mbar_init(bars + B_X * 8, 1); mbar_init(bars + B_Y * 8, 4);
            mbar_init(bars + B_HFULL * 8, 4); mbar_init(bars + B_HFREE * 8, 1);
            l2_prefetch((const char*)P.wq + bid * 6400, 6400);
        }
        bar_sync(6, 256);
        uint4 v[10];
#pragma unroll
        for (int t = 0; t < 10; t++) v[t] = ldg128o(xr + 8 * t);
        if (tid == 224) {
            while ((uint32_t)clock() - t_launch < SLAB_DELAY) {}
            for (int i = 0; i < 3; i++) tma3d(sb + RING_OFF + i * 30720, &tm_wq32, 0, i * 160, cb * 5, bars + B_SLAB * 8);
            PROFW(32);
        }
        __syncwarp();
        mbar_wait(bars + B_WKV * 8, 0);
        PROF(38);
        {
            const uint32_t src = sb + WRAW_OFF + tid * 40, dst = sb + WKV_OFF + (tid >> 3) * 384 + (tid & 7) * 16;
#pragma unroll
            for (int i = 0; i < 3; i++) {
                if (i < 2 || wg == 0) {
                    const uint32_t sa = src + i * 10240, da = dst + i * 12288;
                    const uint2 w0 = lds64(sa), w1 = lds64(sa + 8), w2 = lds64(sa + 16), w3 = lds64(sa + 24), w4 = lds64(sa + 32);
                    sts128(da, w0.x, w0.y, w1.x, w1.y);
                    sts128(da + 128, w2.x, w2.y, w3.x, w3.y);
                    sts64(da + 256, w4.x, w4.y);
                }
            }
        }
        asm volatile("bar.arrive 4, 512;" ::: "memory");
        PROF(37);
        ln_rows<10>(v, lane, xa);
        PROF(39 + wg);
        if (wg == 1) asm volatile("bar.arrive 2, 384;" ::: "memory");
        asm volatile("setmaxnreg.inc.sync.aligned.u32 %0;" :: "n"(NRA));
        uint32_t qa[8], qb[8];
        const uint32_t ec = 0x3F003F00u + __shfl_sync(~0u, lane >> 3, 4);
        qa[6] = __shfl_sync(~0u, lane, 0); qa[7] = __shfl_sync(~0u, lane >> 1, 1); qb[6] = __shfl_sync(~0u, lane >> 2, 2); qb[7] = __shfl_sync(~0u, lane >> 2, 3);
        {
            float d[24];
            mbar_wait(bars + B_SLAB * 8, 0);
            PROF(33 + wg);
            bar_sync(2 + wg, wg ? 256 : 384);
            fence_async_smem();
            const uint64_t dA = mkdesc(sb + XN_OFF, 16, 1024, 1);
            const uint64_t dB = mkdesc(sb + RING_OFF + wg * 10240, 10240, 512, 2);
            wg_fence();
#pragma unroll
            for (int k = 0; k < 30; k++) wgmma_ss_n48(d, dA + (k >> 2) * 512 + (k & 3) * 2, dB + (k / 10) * 1920 + (k % 10) * 64, k != 0);
            wg_commit();
            if (wg == 0) asm volatile("bar.arrive 3, 256;" ::: "memory");
            wg_wait<0>();
            if (lane == 0) mbar_arrive(bars + B_HALF * 8);
            mbar_wait(bars + B_SLAB2 * 8, 0);
            wg_fence();
#pragma unroll
            for (int k = 30; k < 40; k++) wgmma_ss_n48(d, dA + (k >> 2) * 512 + (k & 3) * 2, dB + (k / 10) * 1920 + (k % 10) * 64, 1);
            wg_commit();
            wg_wait<0>();
#pragma unroll
            for (int i = 0; i < 24; i++) asm volatile("" : "+f"(d[i]) :: "memory");
            if (lane == 0) mbar_arrive(bars + B_SLABFREE * 8);
            uint32_t p0[5], p1[5];
#pragma unroll
            for (int i = 0; i < 5; i++) {
                p0[i] = pack_bf16((wg ? d[4 * i + 4] : d[4 * i]) * QSCALE, (wg ? d[4 * i + 5] : d[4 * i + 1]) * QSCALE);
                p1[i] = pack_bf16((wg ? d[4 * i + 6] : d[4 * i + 2]) * QSCALE, (wg ? d[4 * i + 7] : d[4 * i + 3]) * QSCALE);
            }
            qa[0] = p0[0]; qa[1] = p1[0]; qa[2] = p0[1]; qa[3] = p1[1];
            qa[4] = c < 2 ? p0[2] : 0u; qa[5] = c < 2 ? p1[2] : 0u;
            qb[0] = __shfl_xor_sync(~0u, c >= 2 ? p0[2] : p0[3], 2); qb[1] = __shfl_xor_sync(~0u, c >= 2 ? p1[2] : p1[3], 2);
            qb[2] = __shfl_xor_sync(~0u, c >= 2 ? p0[3] : p0[4], 2); qb[3] = __shfl_xor_sync(~0u, c >= 2 ? p1[3] : p1[4], 2);
            qb[4] = __shfl_xor_sync(~0u, c >= 2 ? p0[4] : 0u, 2); qb[5] = __shfl_xor_sync(~0u, c >= 2 ? p1[4] : 0u, 2);
        }
        PROF(1 + wg * 8);

        const uint64_t dK0 = mkdesc(sb + KVR_OFF, 128, 384, 0), dV0 = dK0 + (192u + (16u << 16) - (16ull << 32));
#define LANE_VARS \
        const int tid = fresh_tid(), lane = tid & 31, c = lane & 3; \
        const uint32_t qo_a = sb + QO_OFF + wg * 5120 + warp * 256 + lane * 4; \
        const uint32_t qo_b = qo_a + (c < 2 ? 2056 : 3064);
        float sa[32], sbb[32], oa[12], ob[12];
        uint32_t pa[16], pb[16];
#define QKS wg_fence(); QK0(sa, qa, dK0 + 1152); QK1(sa, qa, dK0 + 1152); wg_commit(); QK0(sbb, qb, dK0 + 1152); QK1(sbb, qb, dK0 + 1152); wg_commit();
#define PUBLISH(h, m) \
            st_pkt(dst + wg * 256 + h * 128, w[6 * h] | m, w[6 * h + 1] | m, w[6 * h + 2] | m, w[6 * h + 3] | m); \
            if (c < 2) st_pkt2((uint2*)(dst + 512 + 2 * h) + wg, w[6 * h + 4] | m, w[6 * h + 5] | m);
#define NORM(o, h, PASS) { \
            _Pragma("unroll") \
            for (int i = 0; i < 12; i++) asm volatile("" : "+f"(o[i]) :: "memory"); \
            const float l0 = __shfl_sync(~0u, o[8], (lane & ~3) | 2), l1 = __shfl_sync(~0u, o[10], (lane & ~3) | 2); \
            const float i0 = rcp(l0), i1 = rcp(l1); \
            _Pragma("unroll") \
            for (int i = 0; i < 6; i++) w[6 * h + i] = pack_bf16(o[2 * i] * ((i & 1) ? i1 : i0), o[2 * i + 1] * ((i & 1) ? i1 : i0)); \
            const uint32_t z = bf2_fma(w[6 * h], 0u, bf2_fma(w[6 * h + 1], 0u, bf2_mul(w[6 * h + 2], 0u))) | bf2_fma(w[6 * h + 3], 0u, bf2_fma(w[6 * h + 4], 0u, bf2_mul(w[6 * h + 5], 0u))); \
            ok = ok && l0 >= 0x1p-102f && l0 <= 8.0e37f && l1 >= 0x1p-102f && l1 <= 8.0e37f && (z & 0x7FFF7FFFu) == 0u;     \
            if (PASS) { const uint32_t m = ok ? 0u : ~0u; PUBLISH(h, m) } }
#define PUT6(a, v, o) sts32(a, v[o]); sts32(a + 128, v[o + 1]); sts32(a + 1024, v[o + 2]); sts32(a + 1152, v[o + 3]); \
            if (c < 2) { sts32(a + 2048, v[o + 4]); sts32(a + 2176, v[o + 5]); }
#define GET6(a, v, o) v[o] = lds32(a); v[o + 1] = lds32(a + 128); v[o + 2] = lds32(a + 1024); v[o + 3] = lds32(a + 1152); \
            v[o + 4] = c < 2 ? lds32(a + 2048) : 0u; v[o + 5] = c < 2 ? lds32(a + 2176) : 0u;
#define OK0 true
#define EPILOGUE(PASS, MID) { \
            LANE_VARS \
            uint4* const dst = P.s->op + bid * 640 + (tid & 127); \
            bool ok = OK0; \
            NORM(oa, 0, PASS) \
            MID \
            NORM(ob, 1, PASS) \
            if (!__all_sync(~0u, ok)) { \
                  \
                if (PASS) { PUT6(qo_a, qa, 0) PUT6(qo_b, qb, 0) } \
                __syncwarp(); \
                mbar_wait(bars + B_KVALL * 8, 0); \
                attn_exact_row((const uint32_t*)g_kv, sb + QO_OFF, warp * 16 + (lane & 15), wg * 40 + (lane >> 4) * 20); \
                __syncwarp(); \
                GET6(qo_a, w, 0) GET6(qo_b, w, 6) \
                if (PASS) { PUBLISH(0, 0u) PUBLISH(1, 0u) } \
                __syncwarp(); \
            } }
#define HANDOVER(PASS) { \
            LANE_VARS \
            PUT6(qo_a, w, 0) PUT6(qo_b, w, 6) \
            if (!PASS) { uint4* const dst = P.s->op + bid * 640 + (tid & 127); PUBLISH(0, ~0u) PUBLISH(1, ~0u) } \
            __syncwarp(); \
            if (lane == 0) mbar_arrive(bars + B_OREADY * 8); }
#define MX(m, a, b) m = __int_as_float(__vimax3_s32(__float_as_int(m), __float_as_int(a), __float_as_int(b)));
#define REF(u, s) { \
            float m0 = -0.f, m1 = -0.f; \
            _Pragma("unroll") \
            for (int i = 0; i < 32; i++) asm volatile("" : "+f"(s[i]) :: "memory"); \
            _Pragma("unroll") \
            for (int j = 0; j < 8; j++) if (FIXED(j)) { MX(m0, s[4 * j], s[4 * j + 1]) MX(m1, s[4 * j + 2], s[4 * j + 3]) } \
            m0 = __fmul_rn(m0 * 0x1p71f, 0x1p71f); m1 = __fmul_rn(m1 * 0x1p71f, 0x1p71f); \
            _Pragma("unroll") \
            for (int j = 0; j < 8; j++) if (!FIXED(j)) { MX(m0, s[4 * j], s[4 * j + 1]) MX(m1, s[4 * j + 2], s[4 * j + 3]) } \
            u = pack_bf16((m0 + 98.f) * -0x1p-64f, (m1 + 98.f) * -0x1p-64f); }
        mbar_wait(bars + (B_KVFULL + 3) * 8, 0);
        PROF(6 + wg * 8);
        QKS
        wg_wait<1>();
        int g4 = 0;
#pragma unroll 1
        do {
            const bool pass = g4 != 0;
            {
                uint32_t ua, ub;
                REF(ua, sa)
                wg_wait<0>();
                if (pass) PROF(2 + wg * 8);
                REF(ub, sbb)
                const uint32_t a1 = __shfl_xor_sync(~0u, ua, 1), a2 = __shfl_xor_sync(~0u, ua, 2), a3 = __shfl_xor_sync(~0u, ua, 3);
                const uint32_t b1 = __shfl_xor_sync(~0u, ub, 1), b2 = __shfl_xor_sync(~0u, ub, 2), b3 = __shfl_xor_sync(~0u, ub, 3);
                ua = bf2_min(bf2_min(ua, a1), bf2_min(a2, a3)); ub = bf2_min(bf2_min(ub, b1), bf2_min(b2, b3));
                const int c = fresh_tid() & 3;
                if (c == 2) {
                    qa[4] = __byte_perm(ua, 0x1F80u, 0x5410); qa[5] = __byte_perm(ua, 0x1F80u, 0x5432);
                    qb[4] = __byte_perm(ub, 0x1F80u, 0x5410); qb[5] = __byte_perm(ub, 0x1F80u, 0x5432);
                }
                if (c == 3) qa[4] = qa[5] = qb[4] = qb[5] = 0x1F80u;
            }
            uint32_t w[12];
            if (pass) EPILOGUE(0, )
#pragma unroll
            for (int i = 0; i < 12; i++) { asm volatile("mov.b32 %0, 0;" : "=f"(oa[i])); asm volatile("mov.b32 %0, 0;" : "=f"(ob[i])); }
            QKS
            if (pass) { HANDOVER(0) PROF(3 + wg * 8); }
            wg_wait<1>();
            if (pass) PROF(7 + wg * 8);
#pragma unroll 1
            do {
#pragma unroll
                for (int j = 0; j < 4; j++) {
                    const auto dV = dV0 + j * 384, dKn = dK0 + j * 384;
                    const uint32_t par = (g4 + (j == 3)) & 1;
#define TRYN const bool nxt = mbar_try(bars + (B_KVFULL + j) * 8, par);
#define ACQN if (!nxt) mbar_wait(bars + (B_KVFULL + j) * 8, par);
#define HALF(s, q, p, o, MID) chunk<0>(s, p, ec, j); chunk<1>(s, p, ec, j); chunk<2>(s, p, ec, j); chunk<3>(s, p, ec, j); MID \
    wg_fence(); PV(o, p, 0, dV); PV(o, p, 1, dV); PV(o, p, 2, dV); PV(o, p, 3, dV); QK0(s, q, dKn); QK1(s, q, dKn); wg_commit(); wg_wait<1>();
#define SWAP(q, a) if (j == 3 && g4 == 7) { LANE_VARS mbar_wait(bars + B_Q2 * 8, 0); \
                        asm volatile("{.reg .pred p; setp.ge.u32 p, %2, 2; @p mov.b32 %0, 0; @p mov.b32 %1, 0;}" : "+r"(q[4]), "+r"(q[5]) : "r"(c)); \
                        exch(q[0], a); exch(q[1], a + 128); exch(q[2], a + 1024); exch(q[3], a + 1152); if (c < 2) { exch(q[4], a + 2048); exch(q[5], a + 2176); } }
                    SWAP(qa, qo_a)
                    TRYN
                    HALF(sa, qa, pa, oa, ACQN)
                    mbar_arrive_if(bars + (B_KVEMPTY + ((j + 3) & 3)) * 8, lane == 0);
                    SWAP(qb, qo_b)
#define TRY2 nxt = mbar_test(bars + (B_KVFULL + ((j + 1) & 3)) * 8, (g4 + (j >= 2)) & 1);
                    HALF(sbb, qb, pb, ob, )
                }
            } while (++g4 & 7);
        } while (g4 < 16);
        {
            uint32_t w[12];
            EPILOGUE(1, mbar_wait(bars + B_Q2 * 8, 1);   wg_wait<0>(); PROF(4 + wg * 8);)
            HANDOVER(1)
        }
        PROF(5 + wg * 8);
        asm volatile("setmaxnreg.dec.sync.aligned.u32 %0;" :: "n"(NRE));
        {
            const int i0 = wg * 160 + (fresh_tid() & 31);
            uint32_t y[20], off[5];
            uint4 x[5];
            float e[40], rr[20];
            mbar_wait(bars + B_Y * 8, 0);
#pragma unroll
            for (int u = 0; u < 5; u++) {
                off[u] = (i0 + 32 * u) / 20 * 16;
                const uint4 v = lds128(sb + Y_OFF(warp) + (i0 + 32 * u) * 16 + off[u]);
                y[4 * u] = v.x; y[4 * u + 1] = v.y; y[4 * u + 2] = v.z; y[4 * u + 3] = v.w;
            }
#pragma unroll
            for (int i = 0; i < 20; i++) {
                e[2 * i] = 1.0f + ex2(fminf(bf_lo(y[i]) * -1.4426950408889634f, 63.0f));
                e[2 * i + 1] = 1.0f + ex2(fminf(bf_hi(y[i]) * -1.4426950408889634f, 63.0f));
                rr[i] = rcp(e[2 * i] * e[2 * i + 1]);
                y[i] = pack_bf16(bf_lo(y[i]) * (e[2 * i + 1] * rr[i]), bf_hi(y[i]) * (e[2 * i] * rr[i]));
            }
            mbar_wait(bars + B_X * 8, 0);
#pragma unroll
            for (int u = 0; u < 5; u++) {
                const uint32_t ch = (i0 + 32 * u) * 16 - off[u] * 20;
                x[u] = lds128(sb + XT_OFF + warp * 1024 + off[u] * 4 + (ch & 48) + (ch >> 6) * 32768);
            }
            char* op = (char*)P.out + (size_t)(rb * 64 + warp * 16) * 1280 + cb * 320;
#pragma unroll
            for (int i = 0; i < 20; i++) asm volatile("" : "+r"(y[i]));
            uint32_t as[5], pin = 0;
#pragma unroll
            for (int u = 0; u < 5; u++) {
                as[u] = __shfl_sync(~0u, sb + S_OFF(warp) + (i0 + 32 * u) * 16 + off[u], i0);
                off[u] = __shfl_sync(~0u, i0 * 16 + off[u] * 60, i0);
                pin |= as[u] | off[u];
            }
            if (wg == 0) PROF(60);
            bar_sync(8 + warp + (pin >> 31), 96);
            uint4 sv[5];
#pragma unroll
            for (int u = 0; u < 5; u++) sv[u] = lds128(as[u]);
#pragma unroll
            for (int u = 0; u < 5; u++)
                *(uint4*)(op + u * 512 + off[u]) = make_uint4(bf2_add(x[u].x, bf2_mul(sv[u].x, y[4 * u])), bf2_add(x[u].y, bf2_mul(sv[u].y, y[4 * u + 1])),
                                                                   bf2_add(x[u].z, bf2_mul(sv[u].z, y[4 * u + 2])), bf2_add(x[u].w, bf2_mul(sv[u].w, y[4 * u + 3])));
            if (wg == 0) PROF(31);
        }
    } else if (wg == 2) {
        const uint64_t dXN = mkdesc(sb + XN_OFF, 16, 1024, 1);
        {
            float d[12];
            const uint64_t dB = mkdesc(sb + WKV_OFF, 384, 128, 0);
            fence_async_smem();
            PROF(43);
            wg_fence();
#pragma unroll
            for (int k = 0; k < 40; k++) wgmma_ss_n24(d, dXN + (k >> 2) * 512 + (k & 3) * 2, dB + k * 48, k != 0);
            wg_commit();
            asm volatile("bar.arrive 2, 384;" ::: "memory");
            PROF(44);
            wg_wait<0>();
            PROF(45);
#pragma unroll
            for (int i = 0; i < 12; i++) asm volatile("" : "+f"(d[i]) :: "memory");
            if ((warp >> 1) == rank) {
                uint32_t* kvb = (uint32_t*)((char*)g_kv + ((rb - (cb < 2)) & 31) * 6144 + warp * 768 + (cb >> 1) * 3072) + lane;
                const bool f0 = cb < 2 && FIXED(8 * rb + 2 * warp), f1 = cb < 2 && FIXED(8 * rb + 2 * warp + 1);
                const float s0 = f0 ? 0x1p-78f : cb < 2 ? 0x1p64f : 1.0f, s1 = f1 ? 0x1p-78f : cb < 2 ? 0x1p64f : 1.0f;
                if (c >= 2) {
                    d[8] = c == 2 ? 1.0f : f0 ? -0.078125f : 0.f; d[9] = c == 2 && f0 ? 126.5f : 0.f;
                    d[10] = c == 2 ? 1.0f : f1 ? -0.078125f : 0.f; d[11] = c == 2 && f1 ? 126.5f : 0.f;
                }
                kvb[0] = pack_bf16(d[0] * s0, d[1] * s0); kvb[96] = pack_bf16(d[2] * s1, d[3] * s1);
                kvb[32] = pack_bf16(d[4] * s0, d[5] * s0); kvb[128] = pack_bf16(d[6] * s1, d[7] * s1);
                kvb[64] = pack_bf16(d[8] * s0, d[9] * s0); kvb[160] = pack_bf16(d[10] * s1, d[11] * s1);
                PROFW(16);
                asm volatile("bar.arrive 5, 128;" ::: "memory");
                __syncwarp();
                if (lane == 0) red_release(&g_flag_kv[rb * FS]);
                __syncwarp();
                PROFW(41);
            } else {
                bar_sync(5, 128);
                if ((warp & 1) == 0 && lane == 0) {
                    mbar_expect_tx(bars + B_SLAB2 * 8, 30720);
                    tma3d(sb + RING_OFF + 92160, &tm_wq32, 0, 480, cb * 5, bars + B_SLAB2 * 8);
                }
                __syncwarp();
            }
        }
        PROF(17);
        asm volatile("setmaxnreg.inc.sync.aligned.u32 %0;" :: "n"(NRG));
        int sl = 3, ph = 0, psl = 0;
        bool ok = false;
#define STAGE(WRAP, NI, GS, DEPTH, first, MMA, UNDER) \
                if (!ok) mbar_wait(bars + (B_RING + sl) * 8, ph); \
                const int csl = sl; \
                if (++sl == 5) { sl = WRAP; ph ^= 1; } \
                _Pragma("unroll") \
                for (int i = 0; i < NI; i++) { \
                    if (i % GS == 0) wg_fence(); \
                    MMA \
                    if (i % GS == GS - 1) { \
                        wg_commit(); \
                        if (i == NI - 1) ok = mbar_test(bars + (B_RING + sl) * 8, ph); \
                        UNDER \
                        wg_wait<DEPTH>(); \
                        if (DEPTH && i == GS * DEPTH - 1) mbar_arrive_if(bars + (B_REMPTY + psl) * 8, lane == 0 && !(first)); \
                        if (!DEPTH && i == NI - 1) mbar_arrive_if(bars + (B_REMPTY + csl) * 8, lane == 0); \
                    } \
                } \
                psl = csl;
#define DRAIN(DEPTH) if (DEPTH) { wg_wait<0>(); mbar_arrive_if(bars + (B_REMPTY + psl) * 8, lane == 0); }
        {
            float d[48];
            const uint64_t dR = mkdesc(sb + SLOT0, 16384 + rank * 64, 1024, 1);
            mbar_wait(bars + (B_RING + 3) * 8, 0);
            fence_async_smem();
#pragma unroll 1
            for (int s = 0; s < 5; s++) {
                const uint64_t dB = dR + sl * 2048, dA = dXN + s * 1024;
                STAGE(2, 8, QG, QD, s == 0, wgmma_ss_n96(d, dA + (i >> 2) * 512 + (i & 3) * 2, dB + i * 128, (s | i) != 0);, )
            }
            DRAIN(QD)
#pragma unroll
            for (int i = 0; i < 48; i++) asm volatile("" : "+f"(d[i]) :: "memory");
            const uint32_t qa_ = sb + QO_OFF + warp * 256 + r * 16 + c * 4;
#pragma unroll
            for (int g = 2; g < 12; g++) {
                const int gs_ = (g == 8 || g == 9) ? g - 8 : g;
                const uint32_t a_ = qa_ + (rank ? (g < 8 ? g + 2 : g < 10 ? g - 6 : g - 10) : g - 2) * 1024;
                sts32(a_, pack_bf16((rank ? d[4 * gs_] : d[4 * g]) * QSCALE, (rank ? d[4 * gs_ + 1] : d[4 * g + 1]) * QSCALE));
                sts32(a_ + 128, pack_bf16((rank ? d[4 * gs_ + 2] : d[4 * g + 2]) * QSCALE, (rank ? d[4 * gs_ + 3] : d[4 * g + 3]) * QSCALE));
            }
            __syncwarp();
            if (lane == 0) mbar_arrive(bars + B_Q2 * 8);
        }
        PROF(18);
#pragma unroll 1
        for (int jj = 0; jj < 3; jj++) {
            float d[64];
            uint32_t g[32];
            const uint64_t dR = mkdesc(sb + SLOT0, 8192, 1024, 1);
#define PROJ \
            _Pragma("unroll 1") \
            for (int kc = 0; kc < 5; kc++) { \
                const uint64_t dB = dR + sl * 2048, dA = dXN + kc * 1024; \
                STAGE(2, 8, FG, FD, kc == 0, wgmma_ss_n128(d, dA + (i >> 2) * 512 + (i & 3) * 2, dB + (i >> 2) * 1024 + (i & 3) * 128, (kc | i) != 0);, ) \
            } \
            DRAIN(FD)
            PROJ
#pragma unroll
            for (int i = 0; i < 64; i++) asm volatile("" : "+f"(d[i]) :: "memory");
#pragma unroll
            for (int i = 0; i < 32; i++) g[i] = pack_bf16(d[2 * i], d[2 * i + 1]);
            PROJ
            mbar_arrive_if(bars + (B_REMPTY + lane) * 8, lane < 2 && jj == 2);
#pragma unroll
            for (int i = 0; i < 64; i++) asm volatile("" : "+f"(d[i]) :: "memory");
            mbar_wait(bars + B_HFREE * 8, jj & 1);
            const int mrow = warp * 16 + ((lane >> 3) & 1) * 8 + (lane & 7);
            const uint32_t ha = sb + HST_OFF + mrow * 128;
#pragma unroll
            for (int j = 0; j < 16; j += 2) {
                uint32_t h[4];
#pragma unroll
                for (int i = 0; i < 4; i++)
                    h[i] = bf2_mul(g[2 * j + i], pack_bf16(d[4 * j + 2 * i], d[4 * j + 2 * i + 1]));
                const int blk = (j & 7) + (lane >> 4);
                stsm4(ha + (j >> 3) * 8192 + ((blk ^ (mrow & 7)) << 4), h[0], h[1], h[2], h[3]);
            }
            fence_async_smem();
            __syncwarp();
            if (lane == 0) mbar_arrive(bars + B_HFULL * 8);
            PROF(19 + jj);
        }
#define ROW_ADDR(base) ((base) + (lane & 15) * 336 + (lane >> 4) * 16 + rank * 64)
#define PUT_ROWS(a0, a1) { \
            _Pragma("unroll") \
            for (int j = 0; j < 10; j++) \
                stsm4((j < 8 ? a0 : a1) + j * 32, pack_bf16(d[8 * j], d[8 * j + 1]), pack_bf16(d[8 * j + 2], d[8 * j + 3]), \
                      pack_bf16(d[8 * j + 4], d[8 * j + 5]), pack_bf16(d[8 * j + 6], d[8 * j + 7])); }
        const uint64_t dRB = mkdesc(sb + SLOT0 + 8192, 1024, 512, 2);
        {
            float d[80];
            const uint64_t dRA = mkdesc(sb + SLOT0, 16, 1024, 1);
#pragma unroll 1
            for (int kc = 0; kc < 24; kc++) {
                const uint64_t dA = dRA + sl * 2048, dB = dRB + sl * 2048;
                STAGE(0, 4, DG, DD, kc == 0, wgmma_ss_n160(d, dA + i * 2, dB + i * 320, (kc | i) != 0);, )
            }
            DRAIN(DD)
#pragma unroll
            for (int i = 0; i < 80; i++) asm volatile("" : "+f"(d[i]) :: "memory");
            const uint32_t ya = ROW_ADDR(sb + Y_OFF(warp));
            PUT_ROWS(ya, ya - rank * 320)
            __syncwarp();
            if (lane == 0) mbar_arrive(bars + B_Y * 8);
        }
        PROF(22);
        PROFV(58, wacc);
        {
            float d[80];
            const uint64_t dRO = mkdesc(sb + SLOT0, 1024, 128, 0);
#pragma unroll 1
            for (int s = 0; s < 5 - DEF; s++) {
                const uint64_t dA = dRO + sl * 2048, dB = dRB + sl * 2048;
                STAGE(0, 4, WG_, WD, s == 0, wgmma_ss_n160(d, dA + i * 128, dB + i * 320, (s | i) != 0);, )
            }
            DRAIN(WD)
            PROF(23);
            const int lane = fresh_tid() & 31;
            const uint4* s0 = P.s->op + rb * 2560 + warp * 32 + lane;
            const uint4 *s1 = s0 + ((cb + 1) & 3) * 640, *s2 = s0 + ((cb + 2) & 3) * 640, *s3 = s0 + ((cb + 3) & 3) * 640;
            asm volatile("" : "+l"(s1), "+l"(s2), "+l"(s3));
            const uint32_t sa0 = __shfl_sync(~0u, ROW_ADDR(sb + S_OFF(warp)), lane), sa1 = __shfl_sync(~0u, ROW_ADDR(sb + S_OFF(warp)) - rank * 320, lane);
            uint4 p1[5], p2[5], p3[5];
#define FETCH(p, s) _Pragma("unroll") for (int k = 0; k < 5; k++) p[k] = ld_pkt(s + k * 128);
#define M3(a, b, c) __vimax3_u32(a, b, c)
#define VALID(p, z) (max(M3(M3(M3(M3(M3(z, p[0].x, p[0].y), p[1].x, p[1].y), p[2].x, p[2].y), p[3].x, p[3].y), p[4].x, p[4].y), \
                         M3(M3(M3(M3(M3(z, p[0].z, p[0].w), p[1].z, p[1].w), p[2].z, p[2].w), p[3].z, p[3].w), p[4].z, p[4].w)) != ~0u)
#define PEER(p, b) if ((DEF == 2 && b == 3) || b >= 4 - LATEW) mbar_wait(bars + (B_RING + 1 + b) * 8, 0); wg_fence(); _Pragma("unroll") for (int k = 0; k < 5; k++) wgmma_rs_n160_t1(d, p[k].x, p[k].y, p[k].z, p[k].w, dRB + (1 + b) * 2048 - 512 + k * 320, 1); wg_commit();
            mbar_wait(bars + B_Q2 * 8, 1);
#pragma unroll
            for (int b = DEF ? -1 : 0; b < (DEF == 2 ? 3 : 4 - LATEW); b++) mbar_wait(bars + (B_RING + 1 + b) * 8, 0);
            if (DEF == 2) mbar_wait(bars + (B_RING + 4) * 8, 1);
            mbar_wait(bars + B_OREADY * 8, 1);
            asm volatile("setmaxnreg.inc.sync.aligned.u32 %0;" :: "n"(512 - 24 - 2 * NRE));
            fence_async_smem();
            FETCH(p1, s1) FETCH(p2, s2) FETCH(p3, s3)
            PROF(28);
            wg_fence();
            if (DEF == 2) {
#pragma unroll
                for (int i = 0; i < 4; i++) wgmma_ss_n160(d, dRO + 4 * 2048 + i * 128, dRB + 4 * 2048 + i * 320, 1);
                wg_commit();
            }
            if (DEF) {
#pragma unroll
                for (int i = 0; i < 4; i++) wgmma_ss_n160(d, dRO + i * 128, dRB + i * 320, 1);
            }
#pragma unroll
            for (int k = 0; k < 5; k++) wgmma_ss_n160(d, mkdesc(sb + QO_OFF, 1024, 128, 0) + k * 128, dRB + 2048 - 512 + k * 320, 1);
            wg_commit();
            if (DEF == 2) { wg_wait<1>(); mbar_arrive_if(bars + (B_REMPTY + 4) * 8, lane == 0); }
            uint32_t pend = 7;
            uint32_t z = (uint32_t)clock() >> 1;
            bool u1 = bar_and(1, 128, VALID(p1, z));
#pragma unroll 1
            for (uint32_t it = 0;; it++) {
                if (u1 && (pend & 1)) { PROF(48); PEER(p1, 1) }
                z = (uint32_t)clock() >> 1;
                const bool u2 = bar_and(1, 128, VALID(p2, z)), u3 = bar_and(1, 128, VALID(p3, z));
                PROF(53 + min(it, 4u));
                if (!u1) { FETCH(p1, s1) }
                if (!u2) { __syncwarp(); FETCH(p2, s2) } else if (pend & 2) { PROF(49); PEER(p2, 2) }
                if (!u3) { FETCH(p3, s3) } else if (pend & 4) { PROF(50); PEER(p3, 3) }
                pend = !u1 | !u2 << 1 | !u3 << 2;
                wg_wait<0>();
                if (!pend) break;
                u1 = bar_and(1, 128, VALID(p1, z));
                if (it > 4000000u) __trap();
            }
#pragma unroll
            for (int i = 0; i < 80; i++) asm volatile("" : "+f"(d[i]) :: "memory");
            PROF(30);
            PUT_ROWS(sa0, sa1)
            asm volatile("bar.arrive %0, 96;" :: "r"(8 + warp) : "memory");
        }
    } else {
        asm volatile("setmaxnreg.dec.sync.aligned.u32 %0;" :: "n"(512 - 2 * NRA - NRG));
        uint32_t epoch;
        asm volatile("ld.relaxed.gpu.global.u32 %0, [%1];" : "=r"(epoch) : "l"(&g_epoch[bid]));
        epoch += 1u;
        if (warp == 3) {
            if (lane == 0) {
                if (SP & 1) {
                    if (SP & 2) while ((uint32_t)clock() - t_launch < PST) __nanosleep(100);
                    for (uint32_t it = 0; (int)(ld_acquire(&g_flag_kv[rb * FS]) - epoch * 8u) < 0; it++) if (it > 4000000u) __trap();
                    uint32_t t = 1u;
                    exch(t, bars + 31 * 8);
                    if (!t) {
                        fence_async_glob();
                        mbar_expect_tx(bars + (B_KVFULL + 3) * 8, 3072);
                        bulk_load(sb + KVR_OFF + 3 * 6144, (const char*)g_kv + KVTILE(31) * 6144, 3072, bars + (B_KVFULL + 3) * 8);
                    }
                }
                mbar_wait(bars + PFB * 8, 0);
                l2_prefetch((const char*)P.wg + bid * 15360, 15360);
                l2_prefetch((const char*)P.wu + bid * 15360, 15360);
                while ((uint32_t)clock() - t_launch < PACK_DELAY) __nanosleep(200);
                mbar_wait(bars + B_SLABFREE * 8, 0);
                char* wpk = (char*)g_w + cb * (136 * 5120);
                mbar_expect_tx(bars + B_PACK * 8, 15360);
                for (int i = 0; i < 3; i++) {
                    tma3d(sb + HST_OFF + i * 5120, &tm_wd, 0, rb * 48 + i * 16, cb * 5 + rank, bars + B_PACK * 8);
                    tma3d(sb + HST_OFF + i * 5120 + 4096, &tm_wdc, 0, rb * 48 + i * 16, cb * 5 + 4 - rank * 4, bars + B_PACK * 8);
                }
                mbar_wait(bars + B_PACK * 8, 0);
                bulk_store(wpk + rb * 15360, sb + HST_OFF, 15360);
                asm volatile("cp.async.bulk.commit_group;" ::: "memory");
                asm volatile("cp.async.bulk.wait_group.read 0;" ::: "memory");
                const int n2 = rb < 8 ? 2 : 1;
                mbar_expect_tx(bars + B_PACK * 8, n2 * 5120);
                for (int i = 0; i < n2; i++) {
                    const int ks = rb + i * 32, u = ks / 10 == cb ? 0 : max(ks % 10 - 5, 0);
                    if (u < 4) {
                        tma3d(sb + HST_OFF + i * 5120, &tm_wo, 0, ks * 16 + u * 4, cb * 5 + rank, bars + B_PACK * 8);
                        tma3d(sb + HST_OFF + i * 5120 + 4096, &tm_woc, 0, ks * 16 + u * 4, cb * 5 + 4 - rank * 4, bars + B_PACK * 8);
                    } else {
                        tma4d(sb + HST_OFF + i * 5120, &tm_wor, 0, 16, ks / 10 * 8 + 4, cb * 5 + rank, bars + B_PACK * 8);
                        tma4d(sb + HST_OFF + i * 5120 + 4096, &tm_worc, 0, 16, ks / 10 * 8 + 4, cb * 5 + 4 - rank * 4, bars + B_PACK * 8);
                    }
                }
                mbar_wait(bars + B_PACK * 8, 1);
                for (int i = 0; i < n2; i++) {
                    const int ks = rb + i * 32;
                    bulk_store(wpk + (96 + ks % 10 / 5 * 20 + ks / 10 * 5 + ks % 5) * 5120, sb + HST_OFF + i * 5120, 5120);
                }
                bulk_commit_wait();
                mbar_arrive(bars + B_HFREE * 8);
                fence_async_glob();
                red_release(&g_flag_w[(cb) * FH]);
                PROFW(52);
            }
            return;
        }
        if (warp == 0) {
            const int tile = KVTILE(lane);
            const uint32_t need = 1u | (3u << lane >> 1);
            bool seen = false, issued = lane >= 4, on = !TWO || lane < 4;
            if (SP & 2) while ((uint32_t)clock() - t_launch < PST) __nanosleep(100);
            for (uint32_t it = 0;; it++) {
                if (!seen && on) seen = (int)(ld_acquire(&g_flag_kv[tile * FS]) - epoch * 8u) >= 0;
                __syncwarp();
                const uint32_t m = __ballot_sync(~0u, seen);
                if (!issued && (m & need) == need) {
                    issued = true;
                    PROFW(35);
                    uint32_t t = 0u;
                    if ((SP & 1) && lane == 0) { t = 1u; exch(t, bars + 31 * 8); }
                    if (!t) {
                    fence_async_glob();
                    const uint32_t slot = (lane + 3) & 3, n = lane ? 6144 : 3072;
                    mbar_expect_tx(bars + (B_KVFULL + slot) * 8, n);
                    bulk_load(sb + KVR_OFF + slot * 6144, (const char*)g_kv + KVTILE(lane + 31) * 6144, n, bars + (B_KVFULL + slot) * 8);
                    }
                }
                if (m == ~0u) break;
                on = on || (m & 15u) == 15u;
                if (it > 4000000u) __trap();
            }
            PROFW(36);
            fence_async_glob();
            __syncwarp();
            {
                if (lane == 0) mbar_arrive(bars + B_KVALL * 8);
                for (int g = 3; g < 64; g++) {
                    mbar_wait(bars + (B_KVEMPTY + (g & 3)) * 8, (((g + 1) >> 2) - 1) & 1);
                    if (elect()) {
                        bulk_load(sb + KVR_OFF + (g & 3) * 6144, (const char*)g_kv + KVTILE(g) * 6144, 6144, bars + (B_KVFULL + (g & 3)) * 8);
                        mbar_expect_tx(bars + (B_KVFULL + (g & 3)) * 8, 6144);
                    }
                }
            }
        } else if (warp == 1) {
            if (lane < 4) asm volatile("prefetch.tensormap [%0];" :: "l"(lane == 0 ? &tm_wq : lane == 1 ? &tm_x : lane == 2 ? &tm_wg : &tm_wu) : "memory");
            mbar_wait(bars + B_HALF * 8, 0);
            int sl = 3, ph = 1;
#define NEXT_SLOT(WRAP, bytes, LOADS) { \
                const uint32_t slot = sb + SLOT0 + sl * 32768, bar = bars + (B_RING + sl) * 8; \
                mbar_wait(bar + (B_REMPTY - B_RING) * 8, ph); \
                if (elect()) { LOADS mbar_expect_tx(bar, bytes); } \
                if (++sl == 5) { sl = WRAP; ph ^= 1; } }
#pragma unroll 1
            for (int s = 0; s < 5; s++) {
                NEXT_SLOT(2, 32768, tma2d(slot, &tm_wq, cb * 160 + 64 + rank * 32, s * 128, bar); tma2d(slot + 16384, &tm_wq, cb * 160 + 128 - rank * 96, s * 128, bar);)
                if (s == 0) { mbar_wait(bars + B_SLABFREE * 8, 0); mbar_wait(bars + (B_KVFULL + RINGWAIT) * 8, 0); }
            }
#pragma unroll 1
            for (int jj = 0; jj < 3; jj++)
#pragma unroll 1
                for (int kc = 0; kc < 10; kc++) {
                    const CUtensorMap* tm = kc < 5 ? &tm_wg : &tm_wu;
                    const int k0 = (kc < 5 ? kc : kc - 5) * 128;
                    NEXT_SLOT(2, 32768, tma3d(slot, tm, 0, k0, cb * 6 + jj * 2, bar); tma3d(slot + 16384, tm, 0, k0 + 64, cb * 6 + jj * 2, bar);)
                }
            const char* wpk = (const char*)g_w + cb * (136 * 5120);
            flag_wait(&g_flag_w[(cb) * FH], epoch * 32u);
#pragma unroll 1
            for (int jj = 0; jj < 3; jj++) {
                flag_wait(&g_flag_h[(rb * 3 + jj) * FH], epoch * 4u);
                PROFW(61 + jj);
                fence_async_glob();
#pragma unroll 1
                for (int i8 = 0; i8 < 8; i8++) {
                    const int kc = (i8 >> 1) * 6 + jj * 2 + (i8 & 1);
                    const char *pw = wpk + kc * 20480, *pa = (const char*)g_h + (size_t)(rb * 24 + kc) * 8192;
                    NEXT_SLOT(0, 28672, bulk_load(slot + 8192, pw, 20480, bar); bulk_load(slot, pa, 8192, bar);)
                }
                if (jj == XJ && elect()) {
                    for (int i = 0; i < 5; i++) tma2d(sb + XT_OFF + i * 32768, &tm_x, cb * 160 + i * 32, rb * 64, bars + B_X * 8);
                    mbar_expect_tx(bars + B_X * 8, 20480);
                }
            }
            flag_wait(&g_flag_o[(rb) * FH], epoch * 4u);
            fence_async_glob();
#pragma unroll 1
            for (int s = 0; s < 5; s++) {
                const char *pw = wpk + (24 + s) * 20480, *pa = (const char*)g_o + (size_t)(rb * 5 + s) * 8192;
                NEXT_SLOT(0, 28672, bulk_load(slot + 8192, pw, 20480, bar); bulk_load(slot, pa, 8192, bar);)
            }
#pragma unroll 1
            for (int s = 0; s < 4; s++) {
                const char* pw = wpk + 116 * 5120 + ((cb + s) & 3) * 25600;
                NEXT_SLOT(0, 25600, bulk_load(slot, pw, 25600, bar);)
            }
        } else {
            if (lane == 0) {
                for (int jj = 0; jj < 3; jj++) {
                    mbar_wait(bars + B_HFULL * 8, jj & 1);
                    bulk_store((char*)g_h + (size_t)(rb * 24 + cb * 6 + jj * 2) * 8192, sb + HST_OFF, 16384);
                    bulk_commit_wait();
                    fence_async_glob();
                    red_release(&g_flag_h[(rb * 3 + jj) * FH]);
                    mbar_arrive(bars + B_HFREE * 8);
                }
                mbar_wait(bars + B_OREADY * 8, 0);
                fence_async_smem();
                bulk_store((char*)g_o + (size_t)(rb * 4 + cb) * 10240, sb + QO_OFF, 10240);
                bulk_commit_wait();
                fence_async_glob();
                red_release(&g_flag_o[(rb) * FH]);
                flag_wait(&g_flag_o[(rb) * FH], epoch * 4u);
                for (int i = 0; i < 4; i++) mbar_arrive(bars + B_Q2 * 8);
                g_epoch[bid] = epoch;
            }
        }
    }
}

typedef CUresult (*EncodeFn)(CUtensorMap*, CUtensorMapDataType, cuuint32_t, void*, const cuuint64_t*, const cuuint64_t*, const cuuint32_t*,
                             const cuuint32_t*, CUtensorMapInterleave, CUtensorMapSwizzle, CUtensorMapL2promotion, CUtensorMapFloatOOBfill);

static void make_map(EncodeFn enc, CUtensorMap* m, const void* base, int K, int N, int grp, int boxk, int ngrp, CUtensorMapSwizzle sw) {
    cuuint32_t es[3] = {1, 1, 1};
    if (ngrp == 0) {
        cuuint64_t dims[2] = {(cuuint64_t)N, (cuuint64_t)K};
        cuuint64_t str[1] = {(cuuint64_t)N * 2};
        cuuint32_t box[2] = {(cuuint32_t)grp, (cuuint32_t)boxk};
        enc(m, CU_TENSOR_MAP_DATA_TYPE_BFLOAT16, 2, (void*)base, dims, str, box, es, CU_TENSOR_MAP_INTERLEAVE_NONE, sw,
            CU_TENSOR_MAP_L2_PROMOTION_L2_128B, CU_TENSOR_MAP_FLOAT_OOB_FILL_NONE);
    } else {
        cuuint64_t dims[3] = {(cuuint64_t)grp, (cuuint64_t)K, (cuuint64_t)(N / grp)};
        cuuint64_t str[2] = {(cuuint64_t)N * 2, (cuuint64_t)grp * 2};
        cuuint32_t box[3] = {(cuuint32_t)grp, (cuuint32_t)boxk, (cuuint32_t)ngrp};
        CUresult rr = enc(m, CU_TENSOR_MAP_DATA_TYPE_BFLOAT16, 3, (void*)base, dims, str, box, es, CU_TENSOR_MAP_INTERLEAVE_NONE, sw,
            CU_TENSOR_MAP_L2_PROMOTION_L2_128B, CU_TENSOR_MAP_FLOAT_OOB_FILL_NONE);
        (void)rr;
    }
}

}

extern "C" void kernel_launch(void* const* d_in, const int* in_sizes, int n_in, void* d_out, int out_size) {
    using namespace mk;
    void* fn = nullptr;
    cudaDriverEntryPointQueryResult qr;
    cudaGetDriverEntryPoint("cuTensorMapEncodeTiled", &fn, cudaEnableDefault, &qr);
    EncodeFn enc = (EncodeFn)fn;
    Params P;
    P.x = (const __nv_bfloat16*)d_in[0]; P.wq = (const __nv_bfloat16*)d_in[1]; P.wk = (const __nv_bfloat16*)d_in[2];
    P.wv = (const __nv_bfloat16*)d_in[3]; P.wo = (const __nv_bfloat16*)d_in[4]; P.wg = (const __nv_bfloat16*)d_in[6];
    P.wu = (const __nv_bfloat16*)d_in[7]; P.wd = (const __nv_bfloat16*)d_in[8]; P.out = (__nv_bfloat16*)d_out;
    cudaGetSymbolAddress((void**)&P.s, g_scratch);
    CUtensorMap tq, tq32, tg, tu, td, to, tdc, toc, tx, tor, torc;
    make_map(enc, &tq, P.wq, 640, 640, 64, 128, 0, CU_TENSOR_MAP_SWIZZLE_128B);
    make_map(enc, &tq32, P.wq, 640, 640, 32, 160, 3, CU_TENSOR_MAP_SWIZZLE_64B);
    make_map(enc, &tg, P.wg, 640, 1536, 64, 64, 2, CU_TENSOR_MAP_SWIZZLE_128B);
    make_map(enc, &tu, P.wu, 640, 1536, 64, 64, 2, CU_TENSOR_MAP_SWIZZLE_128B);
    make_map(enc, &td, P.wd, 1536, 640, 32, 16, 4, CU_TENSOR_MAP_SWIZZLE_64B);
    make_map(enc, &tdc, P.wd, 1536, 640, 32, 16, 1, CU_TENSOR_MAP_SWIZZLE_64B);
    make_map(enc, &to, P.wo, 640, 640, 32, 16, 4, CU_TENSOR_MAP_SWIZZLE_64B);
    make_map(enc, &toc, P.wo, 640, 640, 32, 16, 1, CU_TENSOR_MAP_SWIZZLE_64B);
    make_map(enc, &tx, P.x, 2048, 640, 32, 64, 0, CU_TENSOR_MAP_SWIZZLE_NONE);
    for (int i = 0; i < 2; i++) {
        cuuint64_t dims[4] = {32, 20, 32, 20}, str[3] = {1280, 25600, 64};
        cuuint32_t box[4] = {32, 4, 4, i ? 1u : 4u}, es[4] = {1, 1, 1, 1};
        enc(i ? &torc : &tor, CU_TENSOR_MAP_DATA_TYPE_BFLOAT16, 4, (void*)P.wo, dims, str, box, es, CU_TENSOR_MAP_INTERLEAVE_NONE, CU_TENSOR_MAP_SWIZZLE_64B,
            CU_TENSOR_MAP_L2_PROMOTION_L2_128B, CU_TENSOR_MAP_FLOAT_OOB_FILL_NONE);
    }
    cudaFuncSetAttribute(fused_kernel, cudaFuncAttributeMaxDynamicSharedMemorySize, SMEM_TOTAL);
    fused_kernel<<<128, 512, SMEM_TOTAL, cudaStreamPerThread>>>(P, tq, tq32, tg, tu, td, to, tdc, toc, tx, tor, torc);
}
```
